```python
import torch

def _softmax(x, axis=-1):
    return torch.softmax(x, dim=axis)
def _gelu(x):
    return torch.nn.functional.gelu(x, approximate="tanh")
def _silu(x):
    return torch.nn.functional.silu(x)
def _sigmoid(x):
    return torch.sigmoid(x)
def _layernorm(x, axis=-1, eps=1e-5):
    m = x.mean(dim=axis, keepdim=True)
    v = x.var(dim=axis, keepdim=True, unbiased=False)
    return (x - m) / torch.sqrt(v + eps)
def _scatter_add(tgt, idx, src, axis=0):
    return tgt.clone().index_add_(axis, idx, src)
def _segment_sum(src, seg, n):
    out = torch.zeros((n,) + src.shape[1:], dtype=src.dtype)
    return out.index_add_(0, seg, src)
def _pad(x, pw):
    flat = tuple(v for pair in reversed(pw) for v in pair)
    return torch.nn.functional.pad(x, flat)

kernel_name = 'concat_heads__gqa_block_cached__mha_block_cached__decode'

def setup_inputs():

    _w = (lambda a: (lambda t: t.to(torch.bfloat16) if t.is_floating_point() else t)(torch.as_tensor(a)))
    def _A_setup():
        B, Sq, D = 2, 1, 640
        Hq, Hkv, Sk, Dh = 32, 32, 8192, 192
        assert Hq % Hkv == 0, (Hq, Hkv)
        return {
            "x": _w((lambda *s: torch.randn(*s, dtype=torch.bfloat16) * 0.8)(B, Sq, D)),
            "k_cache": _w((lambda *s: torch.randn(*s, dtype=torch.bfloat16) * 0.8)(B, Hkv, Sk, Dh)),
            "v_cache": _w((lambda *s: torch.randn(*s, dtype=torch.bfloat16) * 0.05)(B, Hkv, Sk, Dh)),
            "wq": _w((lambda *s: torch.randn(*s, dtype=torch.bfloat16) * 0.8)(D, Hq * Dh) * (D ** -0.5)),
            "wo": _w((lambda *s: torch.randn(*s, dtype=torch.bfloat16) * 0.05)(Hq * Dh, D) * ((Hq * Dh) ** -0.5)),
        }
    _A_in = _A_setup()

    def _B_setup():
        B, Sq, D = 2, 1, 640
        H, Sk, Dh = 32, 8192, 192
        return {
            "x": _w((lambda *s: torch.randn(*s, dtype=torch.bfloat16) * 0.8)(B, Sq, D)),
            "k_cache": _w((lambda *s: torch.randn(*s, dtype=torch.bfloat16) * 0.8)(B, H, Sk, Dh)),
            "v_cache": _w((lambda *s: torch.randn(*s, dtype=torch.bfloat16) * 0.05)(B, H, Sk, Dh)),
            "wq": _w((lambda *s: torch.randn(*s, dtype=torch.bfloat16) * 0.8)(D, H * Dh) * (D ** -0.5)),
            "wo": _w((lambda *s: torch.randn(*s, dtype=torch.bfloat16) * 0.05)(H * Dh, D) * ((H * Dh) ** -0.5)),
        }
    _B_in = _B_setup()

    return {
        "A_x": _A_in["x"],
        "A_k_cache": _A_in["k_cache"],
        "A_v_cache": _A_in["v_cache"],
        "A_wq": _A_in["wq"],
        "A_wo": _A_in["wo"],
        "B_x": _B_in["x"],
        "B_k_cache": _B_in["k_cache"],
        "B_v_cache": _B_in["v_cache"],
        "B_wq": _B_in["wq"],
        "B_wo": _B_in["wo"],
    }

def reference(A_x, A_k_cache, A_v_cache, A_wq, A_wo, B_x, B_k_cache, B_v_cache, B_wq, B_wo):
    def _A_ref(x, k_cache, v_cache, wq, wo):
        B, Sq, D = x.shape
        Hq, Dh = 32, 192
        Hkv = k_cache.shape[1]
        rep = Hq // Hkv
        q = (lambda x, *d: x.permute(*d))((x @ wq).reshape(B, Sq, Hq, Dh), 0, 2, 1, 3)
        k = (lambda x, n, axis: torch.repeat_interleave(x, n, dim=axis))(k_cache, rep, axis=1)
        v = (lambda x, n, axis: torch.repeat_interleave(x, n, dim=axis))(v_cache, rep, axis=1)
        scores = torch.einsum("bhqd,bhkd->bhqk", q, k) * (Dh ** -0.5)
        p = _softmax(scores, axis=-1)
        o = torch.einsum("bhqk,bhkd->bhqd", p, v)
        return (lambda x, *d: x.permute(*d))(o, 0, 2, 1, 3).reshape(B, Sq, Hq * Dh) @ wo

    def _B_ref(x, k_cache, v_cache, wq, wo):
        B, Sq, D = x.shape
        H, Dh = 32, 192
        q = (lambda x, *d: x.permute(*d))((x @ wq).reshape(B, Sq, H, Dh), 0, 2, 1, 3)
        scores = torch.einsum("bhqd,bhkd->bhqk", q, k_cache) * (Dh ** -0.5)
        p = _softmax(scores, axis=-1)
        o = torch.einsum("bhqk,bhkd->bhqd", p, v_cache)
        return (lambda x, *d: x.permute(*d))(o, 0, 2, 1, 3).reshape(B, Sq, H * Dh) @ wo

    a = _A_ref(A_x, A_k_cache, A_v_cache, A_wq, A_wo)
    b = _B_ref(B_x, B_k_cache, B_v_cache, B_wq, B_wo)
    return torch.concatenate([a, b], axis=-1)
```

```cpp
#include <cuda.h>
#include <cuda_bf16.h>
#include <cuda_runtime.h>
#include <stdint.h>

namespace {

constexpr int kD = 640;
constexpr int kH = 32;
constexpr int kSk = 8192;
constexpr int kDh = 192;
constexpr int kHD = kH * kDh;

constexpr int kTileKeys = 64;
constexpr int kSlotBytes = kTileKeys * kDh * 2;
constexpr int kSlots = 9;
constexpr int kKvTiles = kSk / kTileKeys;
constexpr int kWqTiles = 5;
constexpr int kWoTiles = 5;
constexpr int kItems = kWqTiles + 2 * kKvTiles + kWoTiles;
constexpr int kConsWarps = 4;
constexpr int kThreads = (kConsWarps + 1) * 32;
constexpr int kSrcPerBranch = 64;
constexpr int kMTiles = kD / 16;

constexpr int kOffRing = 0;
constexpr int kOffBars = kSlots * kSlotBytes;
constexpr int kOffQPart = kOffBars + 256;
constexpr int kOffRedO = kOffQPart + 2 * kDh * 4;
constexpr int kOffRedML = kOffRedO + 4 * kDh * 4;
constexpr int kOffOBuf = kOffRedML + 32;
constexpr int kOffFin = kOffOBuf + 2 * 48 * 4;
constexpr int kOffTicket = kOffFin + 4 * 32 * 4;
constexpr int kSmemUsed = kOffTicket + 16;
constexpr int kSmemBytes = kSmemUsed + 1024;

constexpr uint32_t kSpinLimit = 1u << 22;
#define PACE_DC 240
#define WO_N 3
constexpr int kPaceLead = PACE_DC;
constexpr int kWoDist = WO_N;
constexpr int kPacePolls = 512;

struct Params {
  CUtensorMap k[2], v[2], wq[2], wo[2];
  const __nv_bfloat16* x[2];
  __nv_bfloat16* out;
};

__device__ unsigned long long g_part[2 * kMTiles * kSrcPerBranch * 32];
__device__ unsigned int g_ticket[2 * 32];
__device__ unsigned int g_progress[32];

#define STAMP(i) do { } while (0)
#define GSTAMP(i) do { } while (0)
#define STAMP_ITEM(i) do { } while (0)

__device__ __forceinline__ uint32_t smem_u32(const void* p) { return (uint32_t)__cvta_generic_to_shared(p); }

__device__ __forceinline__ void mbar_init(uint32_t bar, uint32_t cnt) {
  asm volatile("mbarrier.init.shared::cta.b64 [%0], %1;" ::"r"(bar), "r"(cnt) : "memory");
}
__device__ __forceinline__ void mbar_expect_tx(uint32_t bar, uint32_t bytes) {
  asm volatile("mbarrier.arrive.expect_tx.shared::cta.b64 _, [%0], %1;" ::"r"(bar), "r"(bytes) : "memory");
}
__device__ __forceinline__ void mbar_arrive(uint32_t bar) {
  asm volatile("mbarrier.arrive.shared::cta.b64 _, [%0];" ::"r"(bar) : "memory");
}
__device__ __forceinline__ bool mbar_try(uint32_t bar, uint32_t parity) {
  uint32_t ok;
  asm volatile(
      "{\n.reg .pred p;\n"
      "mbarrier.try_wait.parity.shared::cta.b64 p, [%1], %2;\n"
      "selp.u32 %0, 1, 0, p;\n}"
      : "=r"(ok)
      : "r"(bar), "r"(parity)
      : "memory");
  return ok != 0;
}
__device__ __forceinline__ bool mbar_try_cluster(uint32_t bar, uint32_t parity) {
  uint32_t ok;
  asm volatile(
      "{\n.reg .pred p;\n"
      "mbarrier.try_wait.parity.acquire.cluster.shared::cta.b64 p, [%1], %2;\n"
      "selp.u32 %0, 1, 0, p;\n}"
      : "=r"(ok)
      : "r"(bar), "r"(parity)
      : "memory");
  return ok != 0;
}
__device__ __forceinline__ void mbar_wait(uint32_t bar, uint32_t parity) {
  uint32_t n = 0;
  while (!mbar_try(bar, parity)) {
    if (++n > kSpinLimit) __trap();
  }
}
__device__ __forceinline__ void mbar_wait_cluster(uint32_t bar, uint32_t parity) {
  uint32_t n = 0;
  while (!mbar_try_cluster(bar, parity)) {
    if (++n > kSpinLimit) __trap();
  }
}

__device__ __forceinline__ void tma_2d(uint32_t dst, const CUtensorMap* tm, int c0, int c1, uint32_t bar) {
  asm volatile(
      "cp.async.bulk.tensor.2d.shared::cluster.global.mbarrier::complete_tx::bytes [%0], [%1, {%3, %4}], [%2];" ::"r"(dst),
      "l"(tm), "r"(bar), "r"(c0), "r"(c1)
      : "memory");
}
__device__ __forceinline__ void tma_3d(uint32_t dst, const CUtensorMap* tm, int c0, int c1, int c2, uint32_t bar) {
  asm volatile(
      "cp.async.bulk.tensor.3d.shared::cluster.global.mbarrier::complete_tx::bytes [%0], [%1, {%3, %4, %5}], [%2];" ::"r"(dst),
      "l"(tm), "r"(bar), "r"(c0), "r"(c1), "r"(c2)
      : "memory");
}

__device__ __forceinline__ void ldsm4(uint32_t addr, uint32_t (&r)[4]) {
  asm volatile("ldmatrix.sync.aligned.m8n8.x4.shared.b16 {%0,%1,%2,%3}, [%4];"
               : "=r"(r[0]), "=r"(r[1]), "=r"(r[2]), "=r"(r[3])
               : "r"(addr));
}
__device__ __forceinline__ void ldsm4_t(uint32_t addr, uint32_t (&r)[4]) {
  asm volatile("ldmatrix.sync.aligned.m8n8.x4.trans.shared.b16 {%0,%1,%2,%3}, [%4];"
               : "=r"(r[0]), "=r"(r[1]), "=r"(r[2]), "=r"(r[3])
               : "r"(addr));
}
__device__ __forceinline__ void mma_bf16(float (&d)[4], uint32_t a0, uint32_t a1, uint32_t a2, uint32_t a3, uint32_t b0,
                                         uint32_t b1) {
  asm("mma.sync.aligned.m16n8k16.row.col.f32.bf16.bf16.f32 {%0,%1,%2,%3}, {%4,%5,%6,%7}, {%8,%9}, {%0,%1,%2,%3};"
      : "+f"(d[0]), "+f"(d[1]), "+f"(d[2]), "+f"(d[3])
      : "r"(a0), "r"(a1), "r"(a2), "r"(a3), "r"(b0), "r"(b1));
}
__device__ __forceinline__ float ex2(float x) {
  float y;
  asm("ex2.approx.ftz.f32 %0, %1;" : "=f"(y) : "f"(x));
  return y;
}
__device__ __forceinline__ uint32_t pack_bf16(float lo, float hi) {
  uint32_t r;
  asm("cvt.rn.bf16x2.f32 %0, %1, %2;" : "=r"(r) : "f"(hi), "f"(lo));
  return r;
}
__device__ __forceinline__ uint32_t mapa(uint32_t addr, uint32_t rank) {
  uint32_t r;
  asm("mapa.shared::cluster.u32 %0, %1, %2;" : "=r"(r) : "r"(addr), "r"(rank));
  return r;
}
__device__ __forceinline__ void st_async_b32(uint32_t addr, uint32_t val, uint32_t bar) {
  asm volatile("st.async.weak.shared::cluster.mbarrier::complete_tx::bytes.b32 [%0], %1, [%2];" ::"r"(addr), "r"(val),
               "r"(bar)
               : "memory");
}
__device__ __forceinline__ float lds_f32(uint32_t addr) {
  float v;
  asm volatile("ld.shared.f32 %0, [%1];" : "=f"(v) : "r"(addr));
  return v;
}
__device__ __forceinline__ uint32_t lds_u32(uint32_t addr) {
  uint32_t v;
  asm volatile("ld.shared.u32 %0, [%1];" : "=r"(v) : "r"(addr));
  return v;
}
__device__ __forceinline__ float2 lds_f32x2(uint32_t addr) {
  float2 v;
  asm volatile("ld.shared.v2.f32 {%0, %1}, [%2];" : "=f"(v.x), "=f"(v.y) : "r"(addr));
  return v;
}
__device__ __forceinline__ void sts_f32(uint32_t addr, float v) {
  asm volatile("st.shared.f32 [%0], %1;" ::"r"(addr), "f"(v) : "memory");
}
__device__ __forceinline__ void cons_sync() { asm volatile("bar.sync 1, 128;" ::: "memory"); }
__device__ __forceinline__ float sel4(const float (&c)[4], int t) {
  float lo = (t & 1) ? c[1] : c[0];
  float hi = (t & 1) ? c[3] : c[2];
  return (t & 2) ? hi : lo;
}

__global__ void __cluster_dims__(2, 1, 1) __launch_bounds__(kThreads, 1)
    fused_decode_kernel(const __grid_constant__ Params p) {
  extern __shared__ uint8_t smem_raw[];
  const uint32_t sbase = (smem_u32(smem_raw) + 1023u) & ~1023u;
  const uint32_t ring = sbase + kOffRing;
  const uint32_t full0 = sbase + kOffBars;
  const uint32_t empty0 = full0 + 8 * kSlots;
  const uint32_t qbar = empty0 + 8 * kSlots;
  const uint32_t obar = qbar + 8;
  const uint32_t tbar = obar + 8;

  const int warp = threadIdx.x >> 5;
  const int lane = threadIdx.x & 31;
  const int br = blockIdx.x >> 6;
  const int h = (blockIdx.x >> 1) & 31;
  const int b = blockIdx.x & 1;

  if (warp == kConsWarps) {
    const CUtensorMap* tk = &p.k[br];
    const CUtensorMap* tv = &p.v[br];
    const CUtensorMap* twq = &p.wq[br];
    const CUtensorMap* two = &p.wo[br];
    if (lane == 0) {
      GSTAMP(14);
      STAMP(0);
      asm volatile("prefetch.tensormap [%0];" ::"l"(twq) : "memory");
      asm volatile("prefetch.tensormap [%0];" ::"l"(tk) : "memory");
      asm volatile("prefetch.tensormap [%0];" ::"l"(tv) : "memory");
      asm volatile("prefetch.tensormap [%0];" ::"l"(two) : "memory");
#pragma unroll
      for (int i = 0; i < kSlots; i++) {
        mbar_init(full0 + 8 * i, 1);
        mbar_init(empty0 + 8 * i, kConsWarps);
      }
      mbar_init(qbar, 1);
      mbar_init(obar, 1);
      mbar_init(tbar, 1);
      mbar_expect_tx(qbar, 2 * kDh * 4);
      mbar_expect_tx(obar, 2 * 48 * 4);
      asm volatile("fence.mbarrier_init.release.cluster;" ::: "memory");
      asm volatile("fence.proxy.async.shared::cta;" ::: "memory");
    }
    __syncwarp();
    asm volatile("barrier.cluster.arrive.relaxed.aligned;" ::: "memory");
    const int kv_row0 = (b * kH + h) * kSk * 3;
#define ROT 0
    const int tile_rot = (int)blockIdx.x * ROT;
    auto issue = [&](int item, int slot) {
      const uint32_t dst = ring + slot * kSlotBytes;
      const uint32_t bar = full0 + 8 * slot;
      mbar_expect_tx(bar, kSlotBytes);
      if (item < kWqTiles) {
        tma_3d(dst, twq, 0, h * 3, b * 320 + item * 64, bar);
      } else if (item < kWqTiles + 2 * kKvTiles) {
        const int j = item - kWqTiles;
        tma_2d(dst, (j & 1) ? tv : tk, 0, kv_row0 + (((j >> 1) + tile_rot) & (kKvTiles - 1)) * (kTileKeys * 3), bar);
      } else {
        const int j = item - (kWqTiles + 2 * kKvTiles);
        tma_2d(dst, two, j * 128, h * kDh + b * 96, bar);
        tma_2d(dst + kSlotBytes / 2, two, j * 128 + 64, h * kDh + b * 96, bar);
      }
    };
    if (lane == 0) {
      STAMP(10);
      for (int i = 0; i < kSlots; i++) issue(i, i);
      STAMP(11);
    }
    __syncwarp();
    asm volatile("barrier.cluster.wait.acquire.aligned;" ::: "memory");
    if (lane == 0) STAMP(13);
    if (lane == 0) {
      int slot = 0;
      uint32_t ph = 0;
      unsigned int ticket = 0;
      unsigned int seen = 0;
      for (int item = kSlots; item < kItems; item++) {
        mbar_wait(empty0 + 8 * slot, ph);
        const int j = item - kWqTiles;
        if (j < 2 * kKvTiles) {
          int polls = 0;
          while ((int)(seen & 16383u) < j * 64 - kPaceLead && polls < kPacePolls) {
            asm volatile("ld.relaxed.gpu.global.u32 %0, [%1];" : "=r"(seen) : "l"(g_progress) : "memory");
            polls++;
          }
          issue(item, slot);
          asm volatile("ld.relaxed.gpu.global.u32 %0, [%1];" : "=r"(seen) : "l"(g_progress) : "memory");
        } else {
          const int prev = item - kWoDist;
          mbar_wait(full0 + 8 * (prev % kSlots), (prev / kSlots) & 1);
          issue(item, slot);
        }
        if (item == kItems - 24) ticket = atomicAdd(&g_ticket[br * 32], 1u);
        if (item == kItems - 12) {
          asm volatile("st.shared.u32 [%0], %1;" ::"r"(sbase + kOffTicket), "r"(ticket) : "memory");
          mbar_arrive(tbar);
        }
        if (++slot == kSlots) {
          slot = 0;
          ph ^= 1;
        }
      }
      STAMP(1);
    }
  } else {
    const int g = lane >> 2;
    const int t = lane & 3;
    const int mi = lane >> 3;
    const int mr = lane & 7;

    uint32_t xb[20][2];
    {
      const uint32_t* xp = reinterpret_cast<const uint32_t*>(p.x[br] + (g & 1) * kD + b * 320) + t;
#pragma unroll
      for (int kk = 0; kk < 20; kk++) {
        xb[kk][0] = __ldg(xp + kk * 8);
        xb[kk][1] = __ldg(xp + kk * 8 + 4);
      }
    }
    if (threadIdx.x == 0) STAMP(7);
    asm volatile("barrier.cluster.arrive.relaxed.aligned;" ::: "memory");
    asm volatile("barrier.cluster.wait.acquire.aligned;" ::: "memory");
    if (threadIdx.x == 0) STAMP(9);

    uint32_t off[3];
    {
      const int key = (mi >> 1) * 8 + mr;
#pragma unroll
      for (int j = 0; j < 3; j++) {
        const int R = 3 * key + j;
        off[j] = R * 128 + ((((mi & 1) ^ R) & 7) << 4);
      }
    }

    int slot = 0;
    uint32_t ph = 0;
    auto advance = [&]() {
      if (++slot == kSlots) {
        slot = 0;
        ph ^= 1;
      }
    };
    auto release = [&]() {
      __syncwarp();
      if (lane == 0) mbar_arrive(empty0 + 8 * slot);
    };

    uint32_t qa[12][2];
    {
      float acc[3][4];
      uint32_t woff[3];
#pragma unroll
      for (int u = 0; u < 3; u++) {
        acc[u][0] = acc[u][1] = acc[u][2] = acc[u][3] = 0.f;
        const int s = warp * 3 + u;
        const int j = s >> 2;
        const uint32_t o = j == 0 ? off[0] : (j == 1 ? off[1] : off[2]);
        woff[u] = o ^ ((s & 3) << 5);
      }
#pragma unroll
      for (int it = 0; it < kWqTiles; it++) {
        mbar_wait(full0 + 8 * slot, ph);
        STAMP_ITEM(it);
        const uint32_t base = ring + slot * kSlotBytes;
        uint32_t a[4][3][4];
#pragma unroll
        for (int ks = 0; ks < 4; ks++)
#pragma unroll
          for (int u = 0; u < 3; u++) ldsm4_t(base + ks * 6144 + woff[u], a[ks][u]);
        release();
        advance();
#pragma unroll
        for (int ks = 0; ks < 4; ks++)
#pragma unroll
          for (int u = 0; u < 3; u++)
            mma_bf16(acc[u], a[ks][u][0], a[ks][u][1], a[ks][u][2], a[ks][u][3], xb[it * 4 + ks][0], xb[it * 4 + ks][1]);
      }
      const uint32_t dst_rank = t & 1;
      const uint32_t dq = mapa(sbase + kOffQPart + b * (kDh * 4), dst_rank);
      const uint32_t dbar = mapa(qbar, dst_rank);
#pragma unroll
      for (int u = 0; u < 3; u++) {
        const int dim = warp * 48 + u * 16 + g + 8 * (t >> 1);
        st_async_b32(dq + dim * 4, __float_as_uint(sel4(acc[u], t)), dbar);
      }
      mbar_wait_cluster(qbar, 0);
#pragma unroll
      for (int s = 0; s < 12; s++) {
#pragma unroll
        for (int hh = 0; hh < 2; hh++) {
          const uint32_t a0 = sbase + kOffQPart + (16 * s + 8 * hh + 2 * t) * 4;
          const float2 u0 = lds_f32x2(a0);
          const float2 u1 = lds_f32x2(a0 + kDh * 4);
          qa[s][hh] = pack_bf16(u0.x + u1.x, u0.y + u1.y);
        }
      }
    }
    if (threadIdx.x == 0) STAMP(2);

    constexpr float kScaleLog2e = 0.07216878364870322f * 1.4426950408889634f;
    float o[12][4];
#pragma unroll
    for (int s = 0; s < 12; s++) o[s][0] = o[s][1] = o[s][2] = o[s][3] = 0.f;
    float m = -INFINITY, l = 0.f;
    const uint32_t wbase = ring + warp * 6144;

#pragma unroll 1
    for (int tile = 0; tile < kKvTiles; tile++) {
      uint32_t f[12][4];
      mbar_wait(full0 + 8 * slot, ph);
      STAMP_ITEM(kWqTiles + 2 * tile);
      {
        const uint32_t base = wbase + slot * kSlotBytes;
#pragma unroll
        for (int s = 0; s < 12; s++) ldsm4((base + off[s >> 2]) ^ ((s & 3) << 5), f[s]);
      }
      release();
      advance();
      float s0[2][4], s1[2][4];
#pragma unroll
      for (int c = 0; c < 2; c++)
#pragma unroll
        for (int e = 0; e < 4; e++) s0[c][e] = s1[c][e] = 0.f;
#pragma unroll
      for (int s = 0; s < 12; s++) {
        mma_bf16(s0[s & 1], qa[s][0], qa[s][0], qa[s][1], qa[s][1], f[s][0], f[s][1]);
        mma_bf16(s1[s & 1], qa[s][0], qa[s][0], qa[s][1], qa[s][1], f[s][2], f[s][3]);
      }
      const float x0 = s0[0][0] + s0[1][0], x1 = s0[0][1] + s0[1][1];
      const float x2 = s1[0][0] + s1[1][0], x3 = s1[0][1] + s1[1][1];
      float mx = fmaxf(fmaxf(x0, x1), fmaxf(x2, x3));
      mx = fmaxf(mx, __shfl_xor_sync(0xffffffffu, mx, 1));
      mx = fmaxf(mx, __shfl_xor_sync(0xffffffffu, mx, 2));
      if (mx > m) {
        const float alpha = ex2((m - mx) * kScaleLog2e);
        m = mx;
        l *= alpha;
#pragma unroll
        for (int s = 0; s < 12; s++) {
          o[s][0] *= alpha;
          o[s][1] *= alpha;
          o[s][2] *= alpha;
          o[s][3] *= alpha;
        }
      }
      const float mc = m * kScaleLog2e;
      const float p0 = ex2(fmaf(x0, kScaleLog2e, -mc)), p1 = ex2(fmaf(x1, kScaleLog2e, -mc));
      const float p2 = ex2(fmaf(x2, kScaleLog2e, -mc)), p3 = ex2(fmaf(x3, kScaleLog2e, -mc));
      l += (p0 + p1) + (p2 + p3);
      const uint32_t pb0 = pack_bf16(p0, p1), pb1 = pack_bf16(p2, p3);

      mbar_wait(full0 + 8 * slot, ph);
      STAMP_ITEM(kWqTiles + 2 * tile + 1);
      {
        const uint32_t base = wbase + slot * kSlotBytes;
#pragma unroll
        for (int s = 0; s < 12; s++) ldsm4_t((base + off[s >> 2]) ^ ((s & 3) << 5), f[s]);
      }
      release();
      advance();
      if (threadIdx.x == 0) asm volatile("red.relaxed.gpu.global.add.u32 [%0], 1;" ::"l"(g_progress) : "memory");
#pragma unroll
      for (int s = 0; s < 12; s++) mma_bf16(o[s], f[s][0], f[s][1], f[s][2], f[s][3], pb0, pb1);
    }
    if (threadIdx.x == 0) STAMP(3);

    l += __shfl_xor_sync(0xffffffffu, l, 1);
    l += __shfl_xor_sync(0xffffffffu, l, 2);
#pragma unroll
    for (int s = 0; s < 12; s++) {
      if ((s & 3) == t) {
        sts_f32(sbase + kOffRedO + (warp * kDh + s * 16 + g) * 4, o[s][0]);
        sts_f32(sbase + kOffRedO + (warp * kDh + s * 16 + 8 + g) * 4, o[s][2]);
      }
    }
    if (lane == 0) {
      sts_f32(sbase + kOffRedML + warp * 4, m);
      sts_f32(sbase + kOffRedML + 16 + warp * 4, l);
    }
    cons_sync();
    if (threadIdx.x < 96) {
      float mw[4], lw[4];
#pragma unroll
      for (int w = 0; w < 4; w++) {
        mw[w] = lds_f32(sbase + kOffRedML + w * 4);
        lw[w] = lds_f32(sbase + kOffRedML + 16 + w * 4);
      }
      const float mm = fmaxf(fmaxf(mw[0], mw[1]), fmaxf(mw[2], mw[3]));
      float L = 0.f, ox = 0.f, oy = 0.f;
#pragma unroll
      for (int w = 0; w < 4; w++) {
        const float a = ex2((mw[w] - mm) * kScaleLog2e);
        const float2 v = lds_f32x2(sbase + kOffRedO + (w * kDh + 2 * threadIdx.x) * 4);
        L = fmaf(lw[w], a, L);
        ox = fmaf(v.x, a, ox);
        oy = fmaf(v.y, a, oy);
      }
      const float inv = 1.0f / L;
      const uint32_t dst_rank = threadIdx.x >= 48;
      const uint32_t idx = threadIdx.x - 48 * dst_rank;
      st_async_b32(mapa(sbase + kOffOBuf + (b * 48 + idx) * 4, dst_rank), pack_bf16(ox * inv, oy * inv),
                   mapa(obar, dst_rank));
    }
    mbar_wait_cluster(obar, 0);
    uint32_t ob[6][2];
#pragma unroll
    for (int ks = 0; ks < 6; ks++) {
      ob[ks][0] = lds_u32(sbase + kOffOBuf + ((g & 1) * 48 + ks * 8 + t) * 4);
      ob[ks][1] = lds_u32(sbase + kOffOBuf + ((g & 1) * 48 + ks * 8 + 4 + t) * 4);
    }
    mbar_wait(tbar, 0);
    const uint32_t ticket = lds_u32(sbase + kOffTicket);
    const uint32_t tag = (ticket >> 6) + 1;
    const int rank = ticket & 63;
    const int src = blockIdx.x & 63;
    if (threadIdx.x == 0) STAMP(4);

    {
      const uint32_t wo_off = (warp >> 1) * 12288 + ((mi >> 1) * 8 + mr) * 128;
      const uint32_t ch0 = ((4 * (warp & 1) + (mi & 1)) ^ mr) << 4;
      unsigned long long* dst = g_part + ((size_t)(br * kMTiles + 2 * warp) * kSrcPerBranch + src) * 32 + lane;
#pragma unroll 1
      for (int it = 0; it < kWoTiles; it++) {
        mbar_wait(full0 + 8 * slot, ph);
        STAMP_ITEM(kWqTiles + 2 * kKvTiles + it);
        const uint32_t base = ring + slot * kSlotBytes + wo_off;
        uint32_t a[2][6][4];
#pragma unroll
        for (int u = 0; u < 2; u++)
#pragma unroll
          for (int ks = 0; ks < 6; ks++) ldsm4_t(base + ks * 2048 + (ch0 ^ (u << 5)), a[u][ks]);
        advance();
#pragma unroll
        for (int u = 0; u < 2; u++) {
          float acc0[4] = {0.f, 0.f, 0.f, 0.f}, acc1[4] = {0.f, 0.f, 0.f, 0.f};
#pragma unroll
          for (int ks = 0; ks < 6; ks += 2) {
            mma_bf16(acc0, a[u][ks][0], a[u][ks][1], a[u][ks][2], a[u][ks][3], ob[ks][0], ob[ks][1]);
            mma_bf16(acc1, a[u][ks + 1][0], a[u][ks + 1][1], a[u][ks + 1][2], a[u][ks + 1][3], ob[ks + 1][0],
                     ob[ks + 1][1]);
          }
          const float v = sel4(acc0, t) + sel4(acc1, t);
          const unsigned long long w = ((unsigned long long)tag << 32) | __float_as_uint(v);
          asm volatile("st.relaxed.gpu.global.b64 [%0], %1;" ::"l"(dst + (size_t)(it * 8 + u) * (kSrcPerBranch * 32)),
                       "l"(w)
                       : "memory");
        }
      }
    }
    if (threadIdx.x == 0) STAMP(5);

    if (rank >= kSrcPerBranch - kMTiles) {
      const int mt = rank - (kSrcPerBranch - kMTiles);
      const unsigned long long* srcp = g_part + ((size_t)(br * kMTiles + mt) * kSrcPerBranch + warp * 16) * 32 + lane;
      unsigned long long w[16];
#pragma unroll
      for (int j = 0; j < 16; j++) w[j] = 0;
      uint32_t spins = 0;
      while (true) {
        bool ok = true;
#pragma unroll
        for (int j = 0; j < 16; j++) {
          if ((uint32_t)(w[j] >> 32) != tag)
            asm volatile("ld.relaxed.gpu.global.b64 %0, [%1];" : "=l"(w[j]) : "l"(srcp + j * 32) : "memory");
        }
#pragma unroll
        for (int j = 0; j < 16; j++) ok = ok && ((uint32_t)(w[j] >> 32) == tag);
        if (ok) break;
        if (++spins > kSpinLimit) __trap();
      }
      float v = 0.f;
#pragma unroll
      for (int j = 0; j < 16; j++) v += __uint_as_float((uint32_t)w[j]);
      sts_f32(sbase + kOffFin + (warp * 32 + lane) * 4, v);
      cons_sync();
      if (warp == 0) {
        float r = 0.f;
#pragma unroll
        for (int ww = 0; ww < 4; ww++) r += lds_f32(sbase + kOffFin + (ww * 32 + lane) * 4);
        const int col = mt * 16 + g + 8 * (t >> 1);
        p.out[(t & 1) * (2 * kD) + br * kD + col] = __float2bfloat16_rn(r);
      }
    }
    if (threadIdx.x == 0) STAMP(6);
  }
}

typedef CUresult (*EncodeTiledFn)(CUtensorMap*, CUtensorMapDataType, cuuint32_t, void*, const cuuint64_t*,
                                  const cuuint64_t*, const cuuint32_t*, const cuuint32_t*, CUtensorMapInterleave,
                                  CUtensorMapSwizzle, CUtensorMapL2promotion, CUtensorMapFloatOOBfill);

void encode(EncodeTiledFn fn, CUtensorMap* m, const void* base, int rank, const cuuint64_t* dims,
            const cuuint64_t* strides, const cuuint32_t* box) {
  const cuuint32_t es[3] = {1, 1, 1};
  fn(m, CU_TENSOR_MAP_DATA_TYPE_BFLOAT16, rank, const_cast<void*>(base), dims, strides, box, es,
     CU_TENSOR_MAP_INTERLEAVE_NONE, CU_TENSOR_MAP_SWIZZLE_128B, CU_TENSOR_MAP_L2_PROMOTION_NONE,
     CU_TENSOR_MAP_FLOAT_OOB_FILL_NONE);
}

}

extern "C" void kernel_launch(void* const* d_in, const int* in_sizes, int n_in, void* d_out, int out_size) {
  (void)in_sizes;
  (void)n_in;
  (void)out_size;
  static EncodeTiledFn fn = nullptr;
  if (!fn) {
    void* sym = nullptr;
    cudaDriverEntryPointQueryResult qr;
    cudaGetDriverEntryPoint("cuTensorMapEncodeTiled", &sym, cudaEnableDefault, &qr);
    fn = (EncodeTiledFn)sym;
    cudaFuncSetAttribute(fused_decode_kernel, cudaFuncAttributeMaxDynamicSharedMemorySize, kSmemBytes);
  }
  Params p;
  for (int br = 0; br < 2; br++) {
    const void* x = d_in[br * 5 + 0];
    const void* kc = d_in[br * 5 + 1];
    const void* vc = d_in[br * 5 + 2];
    const void* wq = d_in[br * 5 + 3];
    const void* wo = d_in[br * 5 + 4];
    {
      const cuuint64_t dims[2] = {64, (cuuint64_t)2 * kH * kSk * 3};
      const cuuint64_t strides[1] = {128};
      const cuuint32_t box[2] = {64, kTileKeys * 3};
      encode(fn, &p.k[br], kc, 2, dims, strides, box);
      encode(fn, &p.v[br], vc, 2, dims, strides, box);
    }
    {
      const cuuint64_t dims[3] = {64, kHD / 64, kD};
      const cuuint64_t strides[2] = {128, kHD * 2};
      const cuuint32_t box[3] = {64, 3, 64};
      encode(fn, &p.wq[br], wq, 3, dims, strides, box);
    }
    {
      const cuuint64_t dims[2] = {kD, kHD};
      const cuuint64_t strides[1] = {kD * 2};
      const cuuint32_t box[2] = {64, 96};
      encode(fn, &p.wo[br], wo, 2, dims, strides, box);
    }
    p.x[br] = (const __nv_bfloat16*)x;
  }
  p.out = (__nv_bfloat16*)d_out;
  fused_decode_kernel<<<128, kThreads, kSmemBytes>>>(p);
}
```

```cpp
#include <cuda.h>
#include <cuda_bf16.h>
#include <cuda_runtime.h>
#include <stdint.h>

namespace {

constexpr int kD = 640;
constexpr int kH = 32;
constexpr int kSk = 8192;
constexpr int kDh = 192;
constexpr int kHD = kH * kDh;

constexpr int kTileKeys = 64;
constexpr int kSlotBytes = kTileKeys * kDh * 2;
constexpr int kSlots = 9;
constexpr int kKvTiles = kSk / kTileKeys;
constexpr int kWqTiles = 5;
constexpr int kWoTiles = 5;
constexpr int kItems = kWqTiles + 2 * kKvTiles + kWoTiles;
constexpr int kConsWarps = 4;
constexpr int kThreads = (kConsWarps + 1) * 32;
constexpr int kSrcPerBranch = 64;
constexpr int kMTiles = kD / 16;

constexpr int kOffRing = 0;
constexpr int kOffBars = kSlots * kSlotBytes;
constexpr int kOffQPart = kOffBars + 256;
constexpr int kOffRedO = kOffQPart + 2 * kDh * 4;
constexpr int kOffRedML = kOffRedO + 4 * kDh * 4;
constexpr int kOffOBuf = kOffRedML + 32;
constexpr int kOffFin = kOffOBuf + 2 * 48 * 4;
constexpr int kOffTicket = kOffFin + 4 * 32 * 4;
constexpr int kSmemUsed = kOffTicket + 16;
constexpr int kSmemBytes = kSmemUsed + 1024;

constexpr uint32_t kSpinLimit = 1u << 22;
constexpr int kPaceLead = 240;
constexpr int kWoDist = 3;
constexpr int kPaceWrap = 16383;
constexpr int kPacePolls = 512;

struct Params {
  CUtensorMap k[2], v[2], wq[2], wo[2];
  const __nv_bfloat16* x[2];
  __nv_bfloat16* out;
};

__device__ unsigned long long g_part[2 * kMTiles * kSrcPerBranch * 32];
__device__ unsigned int g_ticket[2 * 32];
__device__ unsigned int g_progress[32];


__device__ __forceinline__ uint32_t smem_u32(const void* p) { return (uint32_t)__cvta_generic_to_shared(p); }

__device__ __forceinline__ void mbar_init(uint32_t bar, uint32_t cnt) {
  asm volatile("mbarrier.init.shared::cta.b64 [%0], %1;" ::"r"(bar), "r"(cnt) : "memory");
}
__device__ __forceinline__ void mbar_expect_tx(uint32_t bar, uint32_t bytes) {
  asm volatile("mbarrier.arrive.expect_tx.shared::cta.b64 _, [%0], %1;" ::"r"(bar), "r"(bytes) : "memory");
}
__device__ __forceinline__ void mbar_arrive(uint32_t bar) {
  asm volatile("mbarrier.arrive.shared::cta.b64 _, [%0];" ::"r"(bar) : "memory");
}
__device__ __forceinline__ bool mbar_try(uint32_t bar, uint32_t parity) {
  uint32_t ok;
  asm volatile(
      "{\n.reg .pred p;\n"
      "mbarrier.try_wait.parity.shared::cta.b64 p, [%1], %2;\n"
      "selp.u32 %0, 1, 0, p;\n}"
      : "=r"(ok)
      : "r"(bar), "r"(parity)
      : "memory");
  return ok != 0;
}
__device__ __forceinline__ bool mbar_try_cluster(uint32_t bar, uint32_t parity) {
  uint32_t ok;
  asm volatile(
      "{\n.reg .pred p;\n"
      "mbarrier.try_wait.parity.acquire.cluster.shared::cta.b64 p, [%1], %2;\n"
      "selp.u32 %0, 1, 0, p;\n}"
      : "=r"(ok)
      : "r"(bar), "r"(parity)
      : "memory");
  return ok != 0;
}
__device__ __forceinline__ void mbar_wait(uint32_t bar, uint32_t parity) {
  uint32_t n = 0;
  while (!mbar_try(bar, parity)) {
    if (++n > kSpinLimit) __trap();
  }
}
__device__ __forceinline__ void mbar_wait_cluster(uint32_t bar, uint32_t parity) {
  uint32_t n = 0;
  while (!mbar_try_cluster(bar, parity)) {
    if (++n > kSpinLimit) __trap();
  }
}

__device__ __forceinline__ void tma_2d(uint32_t dst, const CUtensorMap* tm, int c0, int c1, uint32_t bar,
                                       uint64_t pol) {
  asm volatile(
      "cp.async.bulk.tensor.2d.shared::cluster.global.mbarrier::complete_tx::bytes.L2::cache_hint [%0], [%1, {%3, %4}], "
      "[%2], %5;" ::"r"(dst),
      "l"(tm), "r"(bar), "r"(c0), "r"(c1), "l"(pol)
      : "memory");
}
__device__ __forceinline__ void tma_3d(uint32_t dst, const CUtensorMap* tm, int c0, int c1, int c2, uint32_t bar,
                                       uint64_t pol) {
  asm volatile(
      "cp.async.bulk.tensor.3d.shared::cluster.global.mbarrier::complete_tx::bytes.L2::cache_hint [%0], [%1, {%3, %4, "
      "%5}], [%2], %6;" ::"r"(dst),
      "l"(tm), "r"(bar), "r"(c0), "r"(c1), "r"(c2), "l"(pol)
      : "memory");
}

__device__ __forceinline__ void ldsm4(uint32_t addr, uint32_t (&r)[4]) {
  asm volatile("ldmatrix.sync.aligned.m8n8.x4.shared.b16 {%0,%1,%2,%3}, [%4];"
               : "=r"(r[0]), "=r"(r[1]), "=r"(r[2]), "=r"(r[3])
               : "r"(addr));
}
__device__ __forceinline__ void ldsm4_t(uint32_t addr, uint32_t (&r)[4]) {
  asm volatile("ldmatrix.sync.aligned.m8n8.x4.trans.shared.b16 {%0,%1,%2,%3}, [%4];"
               : "=r"(r[0]), "=r"(r[1]), "=r"(r[2]), "=r"(r[3])
               : "r"(addr));
}
__device__ __forceinline__ void mma_bf16(float (&d)[4], uint32_t a0, uint32_t a1, uint32_t a2, uint32_t a3, uint32_t b0,
                                         uint32_t b1) {
  asm("mma.sync.aligned.m16n8k16.row.col.f32.bf16.bf16.f32 {%0,%1,%2,%3}, {%4,%5,%6,%7}, {%8,%9}, {%0,%1,%2,%3};"
      : "+f"(d[0]), "+f"(d[1]), "+f"(d[2]), "+f"(d[3])
      : "r"(a0), "r"(a1), "r"(a2), "r"(a3), "r"(b0), "r"(b1));
}
__device__ __forceinline__ float ex2(float x) {
  float y;
  asm("ex2.approx.ftz.f32 %0, %1;" : "=f"(y) : "f"(x));
  return y;
}
__device__ __forceinline__ uint32_t pack_bf16(float lo, float hi) {
  uint32_t r;
  asm("cvt.rn.bf16x2.f32 %0, %1, %2;" : "=r"(r) : "f"(hi), "f"(lo));
  return r;
}
__device__ __forceinline__ uint32_t mapa(uint32_t addr, uint32_t rank) {
  uint32_t r;
  asm("mapa.shared::cluster.u32 %0, %1, %2;" : "=r"(r) : "r"(addr), "r"(rank));
  return r;
}
__device__ __forceinline__ void st_async_b32(uint32_t addr, uint32_t val, uint32_t bar) {
  asm volatile("st.async.weak.shared::cluster.mbarrier::complete_tx::bytes.b32 [%0], %1, [%2];" ::"r"(addr), "r"(val),
               "r"(bar)
               : "memory");
}
__device__ __forceinline__ float lds_f32(uint32_t addr) {
  float v;
  asm volatile("ld.shared.f32 %0, [%1];" : "=f"(v) : "r"(addr));
  return v;
}
__device__ __forceinline__ uint32_t lds_u32(uint32_t addr) {
  uint32_t v;
  asm volatile("ld.shared.u32 %0, [%1];" : "=r"(v) : "r"(addr));
  return v;
}
__device__ __forceinline__ float2 lds_f32x2(uint32_t addr) {
  float2 v;
  asm volatile("ld.shared.v2.f32 {%0, %1}, [%2];" : "=f"(v.x), "=f"(v.y) : "r"(addr));
  return v;
}
__device__ __forceinline__ void sts_f32(uint32_t addr, float v) {
  asm volatile("st.shared.f32 [%0], %1;" ::"r"(addr), "f"(v) : "memory");
}
__device__ __forceinline__ void cons_sync() { asm volatile("bar.sync 1, 128;" ::: "memory"); }
__device__ __forceinline__ float sel4(const float (&c)[4], int t) {
  float lo = (t & 1) ? c[1] : c[0];
  float hi = (t & 1) ? c[3] : c[2];
  return (t & 2) ? hi : lo;
}

__global__ void __cluster_dims__(2, 1, 1) __launch_bounds__(kThreads, 1)
    fused_decode_kernel(const __grid_constant__ Params p) {
  extern __shared__ uint8_t smem_raw[];
  const uint32_t sbase = (smem_u32(smem_raw) + 1023u) & ~1023u;
  const uint32_t ring = sbase + kOffRing;
  const uint32_t full0 = sbase + kOffBars;
  const uint32_t empty0 = full0 + 8 * kSlots;
  const uint32_t qbar = empty0 + 8 * kSlots;
  const uint32_t obar = qbar + 8;
  const uint32_t tbar = obar + 8;

  const int warp = threadIdx.x >> 5;
  const int lane = threadIdx.x & 31;
  const int br = blockIdx.x >> 6;
  const int h = (blockIdx.x >> 1) & 31;
  const int b = blockIdx.x & 1;

  if (warp == kConsWarps) {
    const CUtensorMap* tk = &p.k[br];
    const CUtensorMap* tv = &p.v[br];
    const CUtensorMap* twq = &p.wq[br];
    const CUtensorMap* two = &p.wo[br];
    const int kv_row0 = (b * kH + h) * kSk * 3;
    const int tile_rot = (int)(((blockIdx.x + 1) * 2654435761u) >> 20);
    if (lane < 4) {
      const CUtensorMap* tm = lane == 0 ? twq : (lane == 1 ? tk : (lane == 2 ? tv : two));
      asm volatile("prefetch.tensormap [%0];" ::"l"(tm) : "memory");
    }
    if (lane == 0) {
#pragma unroll
      for (int i = 0; i < kSlots; i++) {
        mbar_init(full0 + 8 * i, 1);
        mbar_init(empty0 + 8 * i, kConsWarps);
      }
      mbar_init(qbar, 1);
      mbar_init(obar, 1);
      mbar_init(tbar, 1);
      mbar_expect_tx(qbar, 2 * kDh * 4);
      mbar_expect_tx(obar, 2 * 48 * 4);
      asm volatile("fence.mbarrier_init.release.cluster;" ::: "memory");
      asm volatile("fence.proxy.async.shared::cta;" ::: "memory");
    }
    __syncwarp();
    asm volatile("barrier.cluster.arrive.relaxed.aligned;" ::: "memory");
    uint64_t pol;
    asm volatile("createpolicy.fractional.L2::evict_first.b64 %0, 1.0;" : "=l"(pol));
    auto issue = [&](int item, int slot) {
      const uint32_t dst = ring + slot * kSlotBytes;
      const uint32_t bar = full0 + 8 * slot;
      mbar_expect_tx(bar, kSlotBytes);
      if (item < kWqTiles) {
        tma_3d(dst, twq, 0, h * 3, b * 320 + item * 64, bar, pol);
      } else if (item < kWqTiles + 2 * kKvTiles) {
        const int j = item - kWqTiles;
        tma_2d(dst, (j & 1) ? tv : tk, 0, kv_row0 + (((j >> 1) + tile_rot) & (kKvTiles - 1)) * (kTileKeys * 3), bar, pol);
      } else {
        const int j = item - (kWqTiles + 2 * kKvTiles);
        tma_2d(dst, two, j * 128, h * kDh + b * 96, bar, pol);
        tma_2d(dst + kSlotBytes / 2, two, j * 128 + 64, h * kDh + b * 96, bar, pol);
      }
    };
    if (lane == 0) {
      for (int i = 0; i < kSlots; i++) issue(i, i);
    }
    __syncwarp();
    asm volatile("barrier.cluster.wait.acquire.aligned;" ::: "memory");
    if (lane == 0) {
      int slot = 0;
      uint32_t ph = 0;
      unsigned int ticket = 0;
      unsigned int seen = 0;
      for (int item = kSlots; item < kItems; item++) {
        mbar_wait(empty0 + 8 * slot, ph);
        const int j = item - kWqTiles;
        if (j < 2 * kKvTiles) {
          int polls = 0;
          while ((int)(seen & 16383u) < j * 64 - kPaceLead && polls < kPacePolls) {
            asm volatile("ld.relaxed.gpu.global.u32 %0, [%1];" : "=r"(seen) : "l"(g_progress) : "memory");
            polls++;
          }
          issue(item, slot);
          asm volatile("ld.relaxed.gpu.global.u32 %0, [%1];" : "=r"(seen) : "l"(g_progress) : "memory");
        } else {
          const int prev = item - kWoDist;
          mbar_wait(full0 + 8 * (prev % kSlots), (prev / kSlots) & 1);
          issue(item, slot);
        }
        if (item == kItems - 24) ticket = atomicAdd(&g_ticket[br * 32], 1u);
        if (item == kItems - 12) {
          asm volatile("st.shared.u32 [%0], %1;" ::"r"(sbase + kOffTicket), "r"(ticket) : "memory");
          mbar_arrive(tbar);
        }
        if (++slot == kSlots) {
          slot = 0;
          ph ^= 1;
        }
      }
    }
  } else {
    const int g = lane >> 2;
    const int t = lane & 3;
    const int mi = lane >> 3;
    const int mr = lane & 7;

    uint32_t xb[20][2];
    {
      const uint32_t* xp = reinterpret_cast<const uint32_t*>(p.x[br] + (g & 1) * kD + b * 320) + t;
#pragma unroll
      for (int kk = 0; kk < 20; kk++) {
        xb[kk][0] = __ldg(xp + kk * 8);
        xb[kk][1] = __ldg(xp + kk * 8 + 4);
      }
    }
    asm volatile("barrier.cluster.arrive.relaxed.aligned;" ::: "memory");
    asm volatile("barrier.cluster.wait.acquire.aligned;" ::: "memory");

    uint32_t off[3];
    {
      const int key = (mi >> 1) * 8 + mr;
#pragma unroll
      for (int j = 0; j < 3; j++) {
        const int R = 3 * key + j;
        off[j] = R * 128 + ((((mi & 1) ^ R) & 7) << 4);
      }
    }

    int slot = 0;
    uint32_t ph = 0;
    auto advance = [&]() {
      if (++slot == kSlots) {
        slot = 0;
        ph ^= 1;
      }
    };
    auto release = [&]() {
      __syncwarp();
      if (lane == 0) mbar_arrive(empty0 + 8 * slot);
    };

    uint32_t qa[12][2];
    {
      float acc[3][4];
      uint32_t woff[3];
#pragma unroll
      for (int u = 0; u < 3; u++) {
        acc[u][0] = acc[u][1] = acc[u][2] = acc[u][3] = 0.f;
        const int s = warp * 3 + u;
        const int j = s >> 2;
        const uint32_t o = j == 0 ? off[0] : (j == 1 ? off[1] : off[2]);
        woff[u] = o ^ ((s & 3) << 5);
      }
#pragma unroll
      for (int it = 0; it < kWqTiles; it++) {
        mbar_wait(full0 + 8 * slot, ph);
        const uint32_t base = ring + slot * kSlotBytes;
        uint32_t a[4][3][4];
#pragma unroll
        for (int ks = 0; ks < 4; ks++)
#pragma unroll
          for (int u = 0; u < 3; u++) ldsm4_t(base + ks * 6144 + woff[u], a[ks][u]);
        release();
        advance();
#pragma unroll
        for (int ks = 0; ks < 4; ks++)
#pragma unroll
          for (int u = 0; u < 3; u++)
            mma_bf16(acc[u], a[ks][u][0], a[ks][u][1], a[ks][u][2], a[ks][u][3], xb[it * 4 + ks][0], xb[it * 4 + ks][1]);
      }
      const uint32_t dst_rank = t & 1;
      const uint32_t dq = mapa(sbase + kOffQPart + b * (kDh * 4), dst_rank);
      const uint32_t dbar = mapa(qbar, dst_rank);
#pragma unroll
      for (int u = 0; u < 3; u++) {
        const int dim = warp * 48 + u * 16 + g + 8 * (t >> 1);
        st_async_b32(dq + dim * 4, __float_as_uint(sel4(acc[u], t)), dbar);
      }
      mbar_wait_cluster(qbar, 0);
#pragma unroll
      for (int s = 0; s < 12; s++) {
#pragma unroll
        for (int hh = 0; hh < 2; hh++) {
          const uint32_t a0 = sbase + kOffQPart + (16 * s + 8 * hh + 2 * t) * 4;
          const float2 u0 = lds_f32x2(a0);
          const float2 u1 = lds_f32x2(a0 + kDh * 4);
          qa[s][hh] = pack_bf16(u0.x + u1.x, u0.y + u1.y);
        }
      }
    }

    constexpr float kScaleLog2e = 0.07216878364870322f * 1.4426950408889634f;
    float o[12][4];
#pragma unroll
    for (int s = 0; s < 12; s++) o[s][0] = o[s][1] = o[s][2] = o[s][3] = 0.f;
    float m = -INFINITY, l = 0.f;
    const uint32_t wbase = ring + warp * 6144;

    unsigned long long* const part_dst =
        g_part + ((size_t)(br * kMTiles + 2 * warp) * kSrcPerBranch + (blockIdx.x & 63)) * 32 + lane;

    auto clear_parts = [&]() {
#pragma unroll
      for (int i = 0; i < 2 * kWoTiles; i++)
        asm volatile("st.relaxed.gpu.global.b64 [%0], %1;" ::"l"(part_dst + (size_t)((i >> 1) * 8 + (i & 1)) * (kSrcPerBranch * 32)),
                     "l"(0ull)
                     : "memory");
    };

#pragma unroll 1
    for (int tile = 0; tile < kKvTiles; tile++) {
      uint32_t f[12][4];
      mbar_wait(full0 + 8 * slot, ph);
      {
        const uint32_t base = wbase + slot * kSlotBytes;
#pragma unroll
        for (int s = 0; s < 12; s++) ldsm4((base + off[s >> 2]) ^ ((s & 3) << 5), f[s]);
      }
      release();
      advance();
      float s0[2][4], s1[2][4];
#pragma unroll
      for (int c = 0; c < 2; c++)
#pragma unroll
        for (int e = 0; e < 4; e++) s0[c][e] = s1[c][e] = 0.f;
#pragma unroll
      for (int s = 0; s < 12; s++) {
        mma_bf16(s0[s & 1], qa[s][0], qa[s][0], qa[s][1], qa[s][1], f[s][0], f[s][1]);
        mma_bf16(s1[s & 1], qa[s][0], qa[s][0], qa[s][1], qa[s][1], f[s][2], f[s][3]);
      }
      const float x0 = s0[0][0] + s0[1][0], x1 = s0[0][1] + s0[1][1];
      const float x2 = s1[0][0] + s1[1][0], x3 = s1[0][1] + s1[1][1];
      float mx = fmaxf(fmaxf(x0, x1), fmaxf(x2, x3));
      mx = fmaxf(mx, __shfl_xor_sync(0xffffffffu, mx, 1));
      mx = fmaxf(mx, __shfl_xor_sync(0xffffffffu, mx, 2));
      if (mx > m) {
        const float alpha = ex2((m - mx) * kScaleLog2e);
        m = mx;
        l *= alpha;
#pragma unroll
        for (int s = 0; s < 12; s++) {
          o[s][0] *= alpha;
          o[s][1] *= alpha;
          o[s][2] *= alpha;
          o[s][3] *= alpha;
        }
      }
      const float mc = m * kScaleLog2e;
      const float p0 = ex2(fmaf(x0, kScaleLog2e, -mc)), p1 = ex2(fmaf(x1, kScaleLog2e, -mc));
      const float p2 = ex2(fmaf(x2, kScaleLog2e, -mc)), p3 = ex2(fmaf(x3, kScaleLog2e, -mc));
      l += (p0 + p1) + (p2 + p3);
      const uint32_t pb0 = pack_bf16(p0, p1), pb1 = pack_bf16(p2, p3);

      mbar_wait(full0 + 8 * slot, ph);
      {
        const uint32_t base = wbase + slot * kSlotBytes;
#pragma unroll
        for (int s = 0; s < 12; s++) ldsm4_t((base + off[s >> 2]) ^ ((s & 3) << 5), f[s]);
      }
      release();
      advance();
      if (threadIdx.x == 0) asm volatile("red.relaxed.gpu.global.inc.u32 [%0], %1;" ::"l"(g_progress), "n"(kPaceWrap) : "memory");
#pragma unroll
      for (int s = 0; s < 12; s++) mma_bf16(o[s], f[s][0], f[s][1], f[s][2], f[s][3], pb0, pb1);
    }
    clear_parts();

    l += __shfl_xor_sync(0xffffffffu, l, 1);
    l += __shfl_xor_sync(0xffffffffu, l, 2);
#pragma unroll
    for (int s = 0; s < 12; s++) {
      if ((s & 3) == t) {
        sts_f32(sbase + kOffRedO + (warp * kDh + s * 16 + g) * 4, o[s][0]);
        sts_f32(sbase + kOffRedO + (warp * kDh + s * 16 + 8 + g) * 4, o[s][2]);
      }
    }
    if (lane == 0) {
      sts_f32(sbase + kOffRedML + warp * 4, m);
      sts_f32(sbase + kOffRedML + 16 + warp * 4, l);
    }
    cons_sync();
    if (threadIdx.x < 96) {
      float mw[4], lw[4];
#pragma unroll
      for (int w = 0; w < 4; w++) {
        mw[w] = lds_f32(sbase + kOffRedML + w * 4);
        lw[w] = lds_f32(sbase + kOffRedML + 16 + w * 4);
      }
      const float mm = fmaxf(fmaxf(mw[0], mw[1]), fmaxf(mw[2], mw[3]));
      float L = 0.f, ox = 0.f, oy = 0.f;
#pragma unroll
      for (int w = 0; w < 4; w++) {
        const float a = ex2((mw[w] - mm) * kScaleLog2e);
        const float2 v = lds_f32x2(sbase + kOffRedO + (w * kDh + 2 * threadIdx.x) * 4);
        L = fmaf(lw[w], a, L);
        ox = fmaf(v.x, a, ox);
        oy = fmaf(v.y, a, oy);
      }
      const float inv = 1.0f / L;
      const uint32_t dst_rank = threadIdx.x >= 48;
      const uint32_t idx = threadIdx.x - 48 * dst_rank;
      st_async_b32(mapa(sbase + kOffOBuf + (b * 48 + idx) * 4, dst_rank), pack_bf16(ox * inv, oy * inv),
                   mapa(obar, dst_rank));
    }
    mbar_wait_cluster(obar, 0);
    uint32_t ob[6][2];
#pragma unroll
    for (int ks = 0; ks < 6; ks++) {
      ob[ks][0] = lds_u32(sbase + kOffOBuf + ((g & 1) * 48 + ks * 8 + t) * 4);
      ob[ks][1] = lds_u32(sbase + kOffOBuf + ((g & 1) * 48 + ks * 8 + 4 + t) * 4);
    }
    mbar_wait(tbar, 0);
    const uint32_t ticket = lds_u32(sbase + kOffTicket);
    const uint32_t tag = (ticket >> 6) + 1;
    const int rank = ticket & 63;

    {
      const uint32_t wo_off = (warp >> 1) * 12288 + ((mi >> 1) * 8 + mr) * 128;
      const uint32_t ch0 = ((4 * (warp & 1) + (mi & 1)) ^ mr) << 4;
      unsigned long long* const dst = part_dst;
#pragma unroll 1
      for (int it = 0; it < kWoTiles; it++) {
        mbar_wait(full0 + 8 * slot, ph);
        const uint32_t base = ring + slot * kSlotBytes + wo_off;
        uint32_t a[2][6][4];
#pragma unroll
        for (int u = 0; u < 2; u++)
#pragma unroll
          for (int ks = 0; ks < 6; ks++) ldsm4_t(base + ks * 2048 + (ch0 ^ (u << 5)), a[u][ks]);
        advance();
#pragma unroll
        for (int u = 0; u < 2; u++) {
          float acc0[4] = {0.f, 0.f, 0.f, 0.f}, acc1[4] = {0.f, 0.f, 0.f, 0.f};
#pragma unroll
          for (int ks = 0; ks < 6; ks += 2) {
            mma_bf16(acc0, a[u][ks][0], a[u][ks][1], a[u][ks][2], a[u][ks][3], ob[ks][0], ob[ks][1]);
            mma_bf16(acc1, a[u][ks + 1][0], a[u][ks + 1][1], a[u][ks + 1][2], a[u][ks + 1][3], ob[ks + 1][0],
                     ob[ks + 1][1]);
          }
          const float v = sel4(acc0, t) + sel4(acc1, t);
          const unsigned long long w = ((unsigned long long)tag << 32) | __float_as_uint(v);
          asm volatile("st.relaxed.gpu.global.b64 [%0], %1;" ::"l"(dst + (size_t)(it * 8 + u) * (kSrcPerBranch * 32)),
                       "l"(w)
                       : "memory");
        }
      }
    }

    if (rank >= kSrcPerBranch - kMTiles) {
      const int mt = rank - (kSrcPerBranch - kMTiles);
      const unsigned long long* srcp = g_part + ((size_t)(br * kMTiles + mt) * kSrcPerBranch + warp * 16) * 32 + lane;
      unsigned long long w[16];
#pragma unroll
      for (int j = 0; j < 16; j++) w[j] = 0;
      uint32_t spins = 0;
      while (true) {
        bool ok = true;
#pragma unroll
        for (int j = 0; j < 16; j++) {
          if ((uint32_t)(w[j] >> 32) != tag)
            asm volatile("ld.relaxed.gpu.global.b64 %0, [%1];" : "=l"(w[j]) : "l"(srcp + j * 32) : "memory");
        }
#pragma unroll
        for (int j = 0; j < 16; j++) ok = ok && ((uint32_t)(w[j] >> 32) == tag);
        if (ok) break;
        if (++spins > kSpinLimit) __trap();
      }
      float v = 0.f;
#pragma unroll
      for (int j = 0; j < 16; j++) v += __uint_as_float((uint32_t)w[j]);
      sts_f32(sbase + kOffFin + (warp * 32 + lane) * 4, v);
      cons_sync();
      if (warp == 0) {
        float r = 0.f;
#pragma unroll
        for (int ww = 0; ww < 4; ww++) r += lds_f32(sbase + kOffFin + (ww * 32 + lane) * 4);
        const int col = mt * 16 + g + 8 * (t >> 1);
        p.out[(t & 1) * (2 * kD) + br * kD + col] = __float2bfloat16_rn(r);
      }
    }
  }
}

typedef CUresult (*EncodeTiledFn)(CUtensorMap*, CUtensorMapDataType, cuuint32_t, void*, const cuuint64_t*,
                                  const cuuint64_t*, const cuuint32_t*, const cuuint32_t*, CUtensorMapInterleave,
                                  CUtensorMapSwizzle, CUtensorMapL2promotion, CUtensorMapFloatOOBfill);

void encode(EncodeTiledFn fn, CUtensorMap* m, const void* base, int rank, const cuuint64_t* dims,
            const cuuint64_t* strides, const cuuint32_t* box) {
  const cuuint32_t es[3] = {1, 1, 1};
  fn(m, CU_TENSOR_MAP_DATA_TYPE_BFLOAT16, rank, const_cast<void*>(base), dims, strides, box, es,
     CU_TENSOR_MAP_INTERLEAVE_NONE, CU_TENSOR_MAP_SWIZZLE_128B, CU_TENSOR_MAP_L2_PROMOTION_NONE,
     CU_TENSOR_MAP_FLOAT_OOB_FILL_NONE);
}

}

extern "C" void kernel_launch(void* const* d_in, const int* in_sizes, int n_in, void* d_out, int out_size) {
  (void)in_sizes;
  (void)n_in;
  (void)out_size;
  static EncodeTiledFn fn = nullptr;
  if (!fn) {
    void* sym = nullptr;
    cudaDriverEntryPointQueryResult qr;
    cudaGetDriverEntryPoint("cuTensorMapEncodeTiled", &sym, cudaEnableDefault, &qr);
    fn = (EncodeTiledFn)sym;
    cudaFuncSetAttribute(fused_decode_kernel, cudaFuncAttributeMaxDynamicSharedMemorySize, kSmemBytes);
  }
  Params p;
  for (int br = 0; br < 2; br++) {
    const void* x = d_in[br * 5 + 0];
    const void* kc = d_in[br * 5 + 1];
    const void* vc = d_in[br * 5 + 2];
    const void* wq = d_in[br * 5 + 3];
    const void* wo = d_in[br * 5 + 4];
    {
      const cuuint64_t dims[2] = {64, (cuuint64_t)2 * kH * kSk * 3};
      const cuuint64_t strides[1] = {128};
      const cuuint32_t box[2] = {64, kTileKeys * 3};
      encode(fn, &p.k[br], kc, 2, dims, strides, box);
      encode(fn, &p.v[br], vc, 2, dims, strides, box);
    }
    {
      const cuuint64_t dims[3] = {64, kHD / 64, kD};
      const cuuint64_t strides[2] = {128, kHD * 2};
      const cuuint32_t box[3] = {64, 3, 64};
      encode(fn, &p.wq[br], wq, 3, dims, strides, box);
    }
    {
      const cuuint64_t dims[2] = {kD, kHD};
      const cuuint64_t strides[1] = {kD * 2};
      const cuuint32_t box[2] = {64, 96};
      encode(fn, &p.wo[br], wo, 2, dims, strides, box);
    }
    p.x[br] = (const __nv_bfloat16*)x;
  }
  p.out = (__nv_bfloat16*)d_out;
  fused_decode_kernel<<<128, kThreads, kSmemBytes>>>(p);
}
```

```cpp
#include <cuda.h>
#include <cuda_bf16.h>
#include <cuda_runtime.h>
#include <stdint.h>

namespace {

constexpr int kD = 640;
constexpr int kH = 32;
constexpr int kSk = 8192;
constexpr int kDh = 192;
constexpr int kHD = kH * kDh;

constexpr int kTileKeys = 64;
constexpr int kSlotBytes = kTileKeys * kDh * 2;
constexpr int kSlots = 9;
constexpr int kKvTiles = kSk / kTileKeys;
constexpr int kWqTiles = 5;
constexpr int kWoTiles = 5;
constexpr int kItems = kWqTiles + 2 * kKvTiles + kWoTiles;
constexpr int kConsWarps = 4;
constexpr int kThreads = (kConsWarps + 1) * 32;
constexpr int kSrcPerBranch = 64;
constexpr int kMTiles = kD / 16;

constexpr int kOffRing = 0;
constexpr int kOffBars = kSlots * kSlotBytes;
constexpr int kOffQPart = kOffBars + 256;
constexpr int kOffRedO = kOffQPart + 2 * kDh * 4;
constexpr int kOffRedML = kOffRedO + 4 * kDh * 4;
constexpr int kOffOBuf = kOffRedML + 32;
constexpr int kOffFin = kOffOBuf + 2 * 48 * 4;
constexpr int kOffTicket = kOffFin + 4 * 32 * 4;
constexpr int kSmemUsed = kOffTicket + 16;
constexpr int kSmemBytes = kSmemUsed + 1024;

constexpr uint32_t kSpinLimit = 1u << 22;
constexpr int kPaceLead = 232;
constexpr int kWoDist = 3;
constexpr int kPaceWrap = 16383;
constexpr int kPacePolls = 512;

struct Params {
  CUtensorMap k[2], v[2], wq[2], wo[2];
  const __nv_bfloat16* x[2];
  const __nv_bfloat16* wq_ptr[2];
  __nv_bfloat16* out;
};

__device__ unsigned long long g_part[2 * kMTiles * kSrcPerBranch * 32];
__device__ unsigned int g_ticket[2 * 32];
__device__ unsigned int g_progress[32];


__device__ __forceinline__ uint32_t smem_u32(const void* p) { return (uint32_t)__cvta_generic_to_shared(p); }

__device__ __forceinline__ void mbar_init(uint32_t bar, uint32_t cnt) {
  asm volatile("mbarrier.init.shared::cta.b64 [%0], %1;" ::"r"(bar), "r"(cnt) : "memory");
}
__device__ __forceinline__ void mbar_expect_tx(uint32_t bar, uint32_t bytes) {
  asm volatile("mbarrier.arrive.expect_tx.shared::cta.b64 _, [%0], %1;" ::"r"(bar), "r"(bytes) : "memory");
}
__device__ __forceinline__ void mbar_arrive(uint32_t bar) {
  asm volatile("mbarrier.arrive.shared::cta.b64 _, [%0];" ::"r"(bar) : "memory");
}
__device__ __forceinline__ bool mbar_try(uint32_t bar, uint32_t parity) {
  uint32_t ok;
  asm volatile(
      "{\n.reg .pred p;\n"
      "mbarrier.try_wait.parity.shared::cta.b64 p, [%1], %2;\n"
      "selp.u32 %0, 1, 0, p;\n}"
      : "=r"(ok)
      : "r"(bar), "r"(parity)
      : "memory");
  return ok != 0;
}
__device__ __forceinline__ bool mbar_try_cluster(uint32_t bar, uint32_t parity) {
  uint32_t ok;
  asm volatile(
      "{\n.reg .pred p;\n"
      "mbarrier.try_wait.parity.acquire.cluster.shared::cta.b64 p, [%1], %2;\n"
      "selp.u32 %0, 1, 0, p;\n}"
      : "=r"(ok)
      : "r"(bar), "r"(parity)
      : "memory");
  return ok != 0;
}
__device__ __forceinline__ void mbar_wait(uint32_t bar, uint32_t parity) {
  uint32_t n = 0;
  while (!mbar_try(bar, parity)) {
    if (++n > kSpinLimit) __trap();
  }
}
__device__ __forceinline__ void mbar_wait_cluster(uint32_t bar, uint32_t parity) {
  uint32_t n = 0;
  while (!mbar_try_cluster(bar, parity)) {
    if (++n > kSpinLimit) __trap();
  }
}

__device__ __forceinline__ void tma_2d(uint32_t dst, const CUtensorMap* tm, int c0, int c1, uint32_t bar,
                                       uint64_t pol) {
  asm volatile(
      "cp.async.bulk.tensor.2d.shared::cluster.global.mbarrier::complete_tx::bytes.L2::cache_hint [%0], [%1, {%3, %4}], "
      "[%2], %5;" ::"r"(dst),
      "l"(tm), "r"(bar), "r"(c0), "r"(c1), "l"(pol)
      : "memory");
}
__device__ __forceinline__ void tma_3d(uint32_t dst, const CUtensorMap* tm, int c0, int c1, int c2, uint32_t bar,
                                       uint64_t pol) {
  asm volatile(
      "cp.async.bulk.tensor.3d.shared::cluster.global.mbarrier::complete_tx::bytes.L2::cache_hint [%0], [%1, {%3, %4, "
      "%5}], [%2], %6;" ::"r"(dst),
      "l"(tm), "r"(bar), "r"(c0), "r"(c1), "r"(c2), "l"(pol)
      : "memory");
}

__device__ __forceinline__ void ldsm4(uint32_t addr, uint32_t (&r)[4]) {
  asm volatile("ldmatrix.sync.aligned.m8n8.x4.shared.b16 {%0,%1,%2,%3}, [%4];"
               : "=r"(r[0]), "=r"(r[1]), "=r"(r[2]), "=r"(r[3])
               : "r"(addr));
}
__device__ __forceinline__ void ldsm4_t(uint32_t addr, uint32_t (&r)[4]) {
  asm volatile("ldmatrix.sync.aligned.m8n8.x4.trans.shared.b16 {%0,%1,%2,%3}, [%4];"
               : "=r"(r[0]), "=r"(r[1]), "=r"(r[2]), "=r"(r[3])
               : "r"(addr));
}
__device__ __forceinline__ void mma_bf16(float (&d)[4], uint32_t a0, uint32_t a1, uint32_t a2, uint32_t a3, uint32_t b0,
                                         uint32_t b1) {
  asm("mma.sync.aligned.m16n8k16.row.col.f32.bf16.bf16.f32 {%0,%1,%2,%3}, {%4,%5,%6,%7}, {%8,%9}, {%0,%1,%2,%3};"
      : "+f"(d[0]), "+f"(d[1]), "+f"(d[2]), "+f"(d[3])
      : "r"(a0), "r"(a1), "r"(a2), "r"(a3), "r"(b0), "r"(b1));
}
__device__ __forceinline__ float ex2(float x) {
  float y;
  asm("ex2.approx.ftz.f32 %0, %1;" : "=f"(y) : "f"(x));
  return y;
}
__device__ __forceinline__ uint32_t pack_bf16(float lo, float hi) {
  uint32_t r;
  asm("cvt.rn.bf16x2.f32 %0, %1, %2;" : "=r"(r) : "f"(hi), "f"(lo));
  return r;
}
__device__ __forceinline__ float bf16_lo(uint32_t v) { return __uint_as_float(v << 16); }
__device__ __forceinline__ float bf16_hi(uint32_t v) { return __uint_as_float(v & 0xffff0000u); }
__device__ __forceinline__ uint32_t mapa(uint32_t addr, uint32_t rank) {
  uint32_t r;
  asm("mapa.shared::cluster.u32 %0, %1, %2;" : "=r"(r) : "r"(addr), "r"(rank));
  return r;
}
__device__ __forceinline__ void st_async_b32(uint32_t addr, uint32_t val, uint32_t bar) {
  asm volatile("st.async.weak.shared::cluster.mbarrier::complete_tx::bytes.b32 [%0], %1, [%2];" ::"r"(addr), "r"(val),
               "r"(bar)
               : "memory");
}
__device__ __forceinline__ float lds_f32(uint32_t addr) {
  float v;
  asm volatile("ld.shared.f32 %0, [%1];" : "=f"(v) : "r"(addr));
  return v;
}
__device__ __forceinline__ uint32_t lds_u32(uint32_t addr) {
  uint32_t v;
  asm volatile("ld.shared.u32 %0, [%1];" : "=r"(v) : "r"(addr));
  return v;
}
__device__ __forceinline__ float2 lds_f32x2(uint32_t addr) {
  float2 v;
  asm volatile("ld.shared.v2.f32 {%0, %1}, [%2];" : "=f"(v.x), "=f"(v.y) : "r"(addr));
  return v;
}
__device__ __forceinline__ void sts_f32(uint32_t addr, float v) {
  asm volatile("st.shared.f32 [%0], %1;" ::"r"(addr), "f"(v) : "memory");
}
__device__ __forceinline__ void cons_sync() { asm volatile("bar.sync 1, 128;" ::: "memory"); }
__device__ __forceinline__ float sel4(const float (&c)[4], int t) {
  float lo = (t & 1) ? c[1] : c[0];
  float hi = (t & 1) ? c[3] : c[2];
  return (t & 2) ? hi : lo;
}

__global__ void __cluster_dims__(2, 1, 1) __launch_bounds__(kThreads, 1)
    fused_decode_kernel(const __grid_constant__ Params p) {
  extern __shared__ uint8_t smem_raw[];
  const uint32_t sbase = (smem_u32(smem_raw) + 1023u) & ~1023u;
  const uint32_t ring = sbase + kOffRing;
  const uint32_t full0 = sbase + kOffBars;
  const uint32_t empty0 = full0 + 8 * kSlots;
  const uint32_t qbar = empty0 + 8 * kSlots;
  const uint32_t obar = qbar + 8;
  const uint32_t tbar = obar + 8;

  const int warp = threadIdx.x >> 5;
  const int lane = threadIdx.x & 31;
  const int br = blockIdx.x >> 6;
  const int h = (blockIdx.x >> 1) & 31;
  const int b = blockIdx.x & 1;

  if (warp == kConsWarps) {
    const CUtensorMap* tk = &p.k[br];
    const CUtensorMap* tv = &p.v[br];
    const CUtensorMap* twq = &p.wq[br];
    const CUtensorMap* two = &p.wo[br];
    const int kv_row0 = (b * kH + h) * kSk * 3;
    const int tile_rot = (int)(((blockIdx.x + 1) * 2654435761u) >> 20);
    if (lane < 4) {
      const CUtensorMap* tm = lane == 0 ? twq : (lane == 1 ? tk : (lane == 2 ? tv : two));
      asm volatile("prefetch.tensormap [%0];" ::"l"(tm) : "memory");
    }
    if (lane == 0) {
#pragma unroll
      for (int i = 0; i < kSlots; i++) {
        mbar_init(full0 + 8 * i, 1);
        mbar_init(empty0 + 8 * i, kConsWarps);
      }
      mbar_init(qbar, 1);
      mbar_init(obar, 1);
      mbar_init(tbar, 1);
      mbar_expect_tx(qbar, 2 * kDh * 4);
      mbar_expect_tx(obar, 2 * 48 * 4);
      asm volatile("fence.mbarrier_init.release.cluster;" ::: "memory");
      asm volatile("fence.proxy.async.shared::cta;" ::: "memory");
    }
    __syncwarp();
    asm volatile("barrier.cluster.arrive.relaxed.aligned;" ::: "memory");
    uint64_t pol;
    asm volatile("createpolicy.fractional.L2::evict_first.b64 %0, 1.0;" : "=l"(pol));
    auto issue = [&](int item, int slot) {
      const uint32_t dst = ring + slot * kSlotBytes;
      const uint32_t bar = full0 + 8 * slot;
      mbar_expect_tx(bar, kSlotBytes);
      if (item < kWqTiles) {
        tma_3d(dst, twq, 0, h * 3, b * 320 + item * 64, bar, pol);
      } else if (item < kWqTiles + 2 * kKvTiles) {
        const int j = item - kWqTiles;
        tma_2d(dst, (j & 1) ? tv : tk, 0, kv_row0 + (((j >> 1) + tile_rot) & (kKvTiles - 1)) * (kTileKeys * 3), bar, pol);
      } else {
        const int j = item - (kWqTiles + 2 * kKvTiles);
        tma_2d(dst, two, j * 128, h * kDh + b * 96, bar, pol);
        tma_2d(dst + kSlotBytes / 2, two, j * 128 + 64, h * kDh + b * 96, bar, pol);
      }
    };
    if (lane == 0) {
      for (int i = 0; i < kSlots; i++) issue(i, i);
    }
    __syncwarp();
    asm volatile("barrier.cluster.wait.acquire.aligned;" ::: "memory");
    if (lane == 0) {
      int slot = 0;
      uint32_t ph = 0;
      unsigned int ticket = 0;
      unsigned int seen = 0;
      for (int item = kSlots; item < kItems; item++) {
        mbar_wait(empty0 + 8 * slot, ph);
        const int j = item - kWqTiles;
        if (j < 2 * kKvTiles) {
          int polls = 0;
          while ((int)(seen & 16383u) < j * 64 - kPaceLead && polls < kPacePolls) {
            asm volatile("ld.relaxed.gpu.global.u32 %0, [%1];" : "=r"(seen) : "l"(g_progress) : "memory");
            polls++;
          }
          issue(item, slot);
          asm volatile("ld.relaxed.gpu.global.u32 %0, [%1];" : "=r"(seen) : "l"(g_progress) : "memory");
        } else {
          const int prev = item - kWoDist;
          mbar_wait(full0 + 8 * (prev % kSlots), (prev / kSlots) & 1);
          issue(item, slot);
        }
        if (item == kItems - 24) ticket = atomicAdd(&g_ticket[br * 32], 1u);
        if (item == kItems - 12) {
          asm volatile("st.shared.u32 [%0], %1;" ::"r"(sbase + kOffTicket), "r"(ticket) : "memory");
          mbar_arrive(tbar);
        }
        if (++slot == kSlots) {
          slot = 0;
          ph ^= 1;
        }
      }
    }
  } else {
    const int g = lane >> 2;
    const int t = lane & 3;
    const int mi = lane >> 3;
    const int mr = lane & 7;

    {
      const char* w = reinterpret_cast<const char*>(p.wq_ptr[br] + (size_t)(b * 320) * kHD + h * kDh);
#pragma unroll
      for (int k = 0; k < 2; k++) {
        const int ln = threadIdx.x + 128 * k;
        const int row = ln / 3;
        asm volatile("prefetch.global.L2 [%0];" ::"l"(w + (size_t)row * (kHD * 2) + (ln - row * 3) * 128) : "memory");
      }
    }
    uint32_t xb[20][2];
    {
      const uint32_t* xp = reinterpret_cast<const uint32_t*>(p.x[br] + (g & 1) * kD + b * 320) + t;
#pragma unroll
      for (int kk = 0; kk < 20; kk++) {
        xb[kk][0] = __ldg(xp + kk * 8);
        xb[kk][1] = __ldg(xp + kk * 8 + 4);
      }
    }
    asm volatile("barrier.cluster.arrive.relaxed.aligned;" ::: "memory");
    asm volatile("barrier.cluster.wait.acquire.aligned;" ::: "memory");

    uint32_t off[3];
    {
      const int key = (mi >> 1) * 8 + mr;
#pragma unroll
      for (int j = 0; j < 3; j++) {
        const int R = 3 * key + j;
        off[j] = R * 128 + ((((mi & 1) ^ R) & 7) << 4);
      }
    }

    int slot = 0;
    uint32_t ph = 0;
    auto advance = [&]() {
      if (++slot == kSlots) {
        slot = 0;
        ph ^= 1;
      }
    };
    auto release = [&]() {
      __syncwarp();
      if (lane == 0) mbar_arrive(empty0 + 8 * slot);
    };

    uint32_t qa[12][2];
    {
      float acc[3][4];
      uint32_t woff[3];
#pragma unroll
      for (int u = 0; u < 3; u++) {
        acc[u][0] = acc[u][1] = acc[u][2] = acc[u][3] = 0.f;
        const int s = warp * 3 + u;
        const int j = s >> 2;
        const uint32_t o = j == 0 ? off[0] : (j == 1 ? off[1] : off[2]);
        woff[u] = o ^ ((s & 3) << 5);
      }
#pragma unroll
      for (int it = 0; it < kWqTiles; it++) {
        mbar_wait(full0 + 8 * slot, ph);
        const uint32_t base = ring + slot * kSlotBytes;
        uint32_t a[4][3][4];
#pragma unroll
        for (int ks = 0; ks < 4; ks++)
#pragma unroll
          for (int u = 0; u < 3; u++) ldsm4_t(base + ks * 6144 + woff[u], a[ks][u]);
        release();
        advance();
#pragma unroll
        for (int ks = 0; ks < 4; ks++)
#pragma unroll
          for (int u = 0; u < 3; u++)
            mma_bf16(acc[u], a[ks][u][0], a[ks][u][1], a[ks][u][2], a[ks][u][3], xb[it * 4 + ks][0], xb[it * 4 + ks][1]);
      }
      const uint32_t dst_rank = t & 1;
      const uint32_t dq = mapa(sbase + kOffQPart + b * (kDh * 4), dst_rank);
      const uint32_t dbar = mapa(qbar, dst_rank);
#pragma unroll
      for (int u = 0; u < 3; u++) {
        const int dim = warp * 48 + u * 16 + g + 8 * (t >> 1);
        st_async_b32(dq + dim * 4, __float_as_uint(sel4(acc[u], t)), dbar);
      }
      mbar_wait_cluster(qbar, 0);
#pragma unroll
      for (int s = 0; s < 12; s++) {
#pragma unroll
        for (int hh = 0; hh < 2; hh++) {
          const uint32_t a0 = sbase + kOffQPart + (16 * s + 8 * hh + 2 * t) * 4;
          const float2 u0 = lds_f32x2(a0);
          const float2 u1 = lds_f32x2(a0 + kDh * 4);
          qa[s][hh] = pack_bf16(u0.x + u1.x, u0.y + u1.y);
        }
      }
    }

    constexpr float kScale = 0.07216878364870322f;
    constexpr float kLog2e = 1.4426950408889634f;
    float o[12][4];
#pragma unroll
    for (int s = 0; s < 12; s++) o[s][0] = o[s][1] = o[s][2] = o[s][3] = 0.f;
    float m = -INFINITY, l = 0.f;
    const uint32_t wbase = ring + warp * 6144;

    unsigned long long* const part_dst =
        g_part + ((size_t)(br * kMTiles + 2 * warp) * kSrcPerBranch + (blockIdx.x & 63)) * 32 + lane;

    auto clear_parts = [&]() {
#pragma unroll
      for (int i = 0; i < 2 * kWoTiles; i++)
        asm volatile("st.relaxed.gpu.global.b64 [%0], %1;" ::"l"(part_dst + (size_t)((i >> 1) * 8 + (i & 1)) * (kSrcPerBranch * 32)),
                     "l"(0ull)
                     : "memory");
    };

#pragma unroll 1
    for (int tile = 0; tile < kKvTiles; tile++) {
      uint32_t f[12][4];
      mbar_wait(full0 + 8 * slot, ph);
      {
        const uint32_t base = wbase + slot * kSlotBytes;
#pragma unroll
        for (int s = 0; s < 12; s++) ldsm4((base + off[s >> 2]) ^ ((s & 3) << 5), f[s]);
      }
      release();
      advance();
      float s0[2][4], s1[2][4];
#pragma unroll
      for (int c = 0; c < 2; c++)
#pragma unroll
        for (int e = 0; e < 4; e++) s0[c][e] = s1[c][e] = 0.f;
#pragma unroll
      for (int s = 0; s < 12; s++) {
        mma_bf16(s0[s & 1], qa[s][0], qa[s][0], qa[s][1], qa[s][1], f[s][0], f[s][1]);
        mma_bf16(s1[s & 1], qa[s][0], qa[s][0], qa[s][1], qa[s][1], f[s][2], f[s][3]);
      }
      const uint32_t r01 = pack_bf16(s0[0][0] + s0[1][0], s0[0][1] + s0[1][1]);
      const uint32_t r23 = pack_bf16(s1[0][0] + s1[1][0], s1[0][1] + s1[1][1]);
      const uint32_t t01 = pack_bf16(bf16_lo(r01) * kScale, bf16_hi(r01) * kScale);
      const uint32_t t23 = pack_bf16(bf16_lo(r23) * kScale, bf16_hi(r23) * kScale);
      const float x0 = bf16_lo(t01), x1 = bf16_hi(t01), x2 = bf16_lo(t23), x3 = bf16_hi(t23);
      float mx = fmaxf(fmaxf(x0, x1), fmaxf(x2, x3));
      mx = fmaxf(mx, __shfl_xor_sync(0xffffffffu, mx, 1));
      mx = fmaxf(mx, __shfl_xor_sync(0xffffffffu, mx, 2));
      if (mx > m) {
        const float alpha = ex2((m - mx) * kLog2e);
        m = mx;
        l *= alpha;
#pragma unroll
        for (int s = 0; s < 12; s++) {
          o[s][0] *= alpha;
          o[s][1] *= alpha;
          o[s][2] *= alpha;
          o[s][3] *= alpha;
        }
      }
      const float p0 = ex2((x0 - m) * kLog2e), p1 = ex2((x1 - m) * kLog2e);
      const float p2 = ex2((x2 - m) * kLog2e), p3 = ex2((x3 - m) * kLog2e);
      l += (p0 + p1) + (p2 + p3);
      const uint32_t pb0 = pack_bf16(p0, p1), pb1 = pack_bf16(p2, p3);

      mbar_wait(full0 + 8 * slot, ph);
      {
        const uint32_t base = wbase + slot * kSlotBytes;
#pragma unroll
        for (int s = 0; s < 12; s++) ldsm4_t((base + off[s >> 2]) ^ ((s & 3) << 5), f[s]);
      }
      release();
      advance();
      if (threadIdx.x == 0) asm volatile("red.relaxed.gpu.global.inc.u32 [%0], %1;" ::"l"(g_progress), "n"(kPaceWrap) : "memory");
#pragma unroll
      for (int s = 0; s < 12; s++) mma_bf16(o[s], f[s][0], f[s][1], f[s][2], f[s][3], pb0, pb1);
    }
    clear_parts();

    l += __shfl_xor_sync(0xffffffffu, l, 1);
    l += __shfl_xor_sync(0xffffffffu, l, 2);
#pragma unroll
    for (int s = 0; s < 12; s++) {
      if ((s & 3) == t) {
        sts_f32(sbase + kOffRedO + (warp * kDh + s * 16 + g) * 4, o[s][0]);
        sts_f32(sbase + kOffRedO + (warp * kDh + s * 16 + 8 + g) * 4, o[s][2]);
      }
    }
    if (lane == 0) {
      sts_f32(sbase + kOffRedML + warp * 4, m);
      sts_f32(sbase + kOffRedML + 16 + warp * 4, l);
    }
    cons_sync();
    if (threadIdx.x < 96) {
      float mw[4], lw[4];
#pragma unroll
      for (int w = 0; w < 4; w++) {
        mw[w] = lds_f32(sbase + kOffRedML + w * 4);
        lw[w] = lds_f32(sbase + kOffRedML + 16 + w * 4);
      }
      const float mm = fmaxf(fmaxf(mw[0], mw[1]), fmaxf(mw[2], mw[3]));
      float L = 0.f, ox = 0.f, oy = 0.f;
#pragma unroll
      for (int w = 0; w < 4; w++) {
        const float a = ex2((mw[w] - mm) * kLog2e);
        const float2 v = lds_f32x2(sbase + kOffRedO + (w * kDh + 2 * threadIdx.x) * 4);
        L = fmaf(lw[w], a, L);
        ox = fmaf(v.x, a, ox);
        oy = fmaf(v.y, a, oy);
      }
      const float inv = 1.0f / L;
      const uint32_t dst_rank = threadIdx.x >= 48;
      const uint32_t idx = threadIdx.x - 48 * dst_rank;
      st_async_b32(mapa(sbase + kOffOBuf + (b * 48 + idx) * 4, dst_rank), pack_bf16(ox * inv, oy * inv),
                   mapa(obar, dst_rank));
    }
    mbar_wait_cluster(obar, 0);
    uint32_t ob[6][2];
#pragma unroll
    for (int ks = 0; ks < 6; ks++) {
      ob[ks][0] = lds_u32(sbase + kOffOBuf + ((g & 1) * 48 + ks * 8 + t) * 4);
      ob[ks][1] = lds_u32(sbase + kOffOBuf + ((g & 1) * 48 + ks * 8 + 4 + t) * 4);
    }
    mbar_wait(tbar, 0);
    const uint32_t ticket = lds_u32(sbase + kOffTicket);
    const uint32_t tag = (ticket >> 6) + 1;
    const int rank = ticket & 63;

    {
      const uint32_t wo_off = (warp >> 1) * 12288 + ((mi >> 1) * 8 + mr) * 128;
      const uint32_t ch0 = ((4 * (warp & 1) + (mi & 1)) ^ mr) << 4;
      unsigned long long* const dst = part_dst;
#pragma unroll 1
      for (int it = 0; it < kWoTiles; it++) {
        mbar_wait(full0 + 8 * slot, ph);
        const uint32_t base = ring + slot * kSlotBytes + wo_off;
        uint32_t a[2][6][4];
#pragma unroll
        for (int u = 0; u < 2; u++)
#pragma unroll
          for (int ks = 0; ks < 6; ks++) ldsm4_t(base + ks * 2048 + (ch0 ^ (u << 5)), a[u][ks]);
        advance();
#pragma unroll
        for (int u = 0; u < 2; u++) {
          float acc0[4] = {0.f, 0.f, 0.f, 0.f}, acc1[4] = {0.f, 0.f, 0.f, 0.f};
#pragma unroll
          for (int ks = 0; ks < 6; ks += 2) {
            mma_bf16(acc0, a[u][ks][0], a[u][ks][1], a[u][ks][2], a[u][ks][3], ob[ks][0], ob[ks][1]);
            mma_bf16(acc1, a[u][ks + 1][0], a[u][ks + 1][1], a[u][ks + 1][2], a[u][ks + 1][3], ob[ks + 1][0],
                     ob[ks + 1][1]);
          }
          const float v = sel4(acc0, t) + sel4(acc1, t);
          const unsigned long long w = ((unsigned long long)tag << 32) | __float_as_uint(v);
          asm volatile("st.relaxed.gpu.global.b64 [%0], %1;" ::"l"(dst + (size_t)(it * 8 + u) * (kSrcPerBranch * 32)),
                       "l"(w)
                       : "memory");
        }
      }
    }

    if (rank >= kSrcPerBranch - kMTiles) {
      const int mt = rank - (kSrcPerBranch - kMTiles);
      const unsigned long long* srcp = g_part + ((size_t)(br * kMTiles + mt) * kSrcPerBranch + warp * 16) * 32 + lane;
      unsigned long long w[16];
#pragma unroll
      for (int j = 0; j < 16; j++) w[j] = 0;
      uint32_t spins = 0;
      while (true) {
        bool ok = true;
#pragma unroll
        for (int j = 0; j < 16; j++) {
          if ((uint32_t)(w[j] >> 32) != tag)
            asm volatile("ld.relaxed.gpu.global.b64 %0, [%1];" : "=l"(w[j]) : "l"(srcp + j * 32) : "memory");
        }
#pragma unroll
        for (int j = 0; j < 16; j++) ok = ok && ((uint32_t)(w[j] >> 32) == tag);
        if (ok) break;
        if (++spins > kSpinLimit) __trap();
      }
      float v = 0.f;
#pragma unroll
      for (int j = 0; j < 16; j++) v += __uint_as_float((uint32_t)w[j]);
      sts_f32(sbase + kOffFin + (warp * 32 + lane) * 4, v);
      cons_sync();
      if (warp == 0) {
        float r = 0.f;
#pragma unroll
        for (int ww = 0; ww < 4; ww++) r += lds_f32(sbase + kOffFin + (ww * 32 + lane) * 4);
        const int col = mt * 16 + g + 8 * (t >> 1);
        p.out[(t & 1) * (2 * kD) + br * kD + col] = __float2bfloat16_rn(r);
      }
    }
  }
}

typedef CUresult (*EncodeTiledFn)(CUtensorMap*, CUtensorMapDataType, cuuint32_t, void*, const cuuint64_t*,
                                  const cuuint64_t*, const cuuint32_t*, const cuuint32_t*, CUtensorMapInterleave,
                                  CUtensorMapSwizzle, CUtensorMapL2promotion, CUtensorMapFloatOOBfill);

void encode(EncodeTiledFn fn, CUtensorMap* m, const void* base, int rank, const cuuint64_t* dims,
            const cuuint64_t* strides, const cuuint32_t* box) {
  const cuuint32_t es[3] = {1, 1, 1};
  fn(m, CU_TENSOR_MAP_DATA_TYPE_BFLOAT16, rank, const_cast<void*>(base), dims, strides, box, es,
     CU_TENSOR_MAP_INTERLEAVE_NONE, CU_TENSOR_MAP_SWIZZLE_128B, CU_TENSOR_MAP_L2_PROMOTION_NONE,
     CU_TENSOR_MAP_FLOAT_OOB_FILL_NONE);
}

}

extern "C" void kernel_launch(void* const* d_in, const int* in_sizes, int n_in, void* d_out, int out_size) {
  (void)in_sizes;
  (void)n_in;
  (void)out_size;
  static EncodeTiledFn fn = nullptr;
  if (!fn) {
    void* sym = nullptr;
    cudaDriverEntryPointQueryResult qr;
    cudaGetDriverEntryPoint("cuTensorMapEncodeTiled", &sym, cudaEnableDefault, &qr);
    fn = (EncodeTiledFn)sym;
    cudaFuncSetAttribute(fused_decode_kernel, cudaFuncAttributeMaxDynamicSharedMemorySize, kSmemBytes);
  }
  Params p;
  for (int br = 0; br < 2; br++) {
    const void* x = d_in[br * 5 + 0];
    const void* kc = d_in[br * 5 + 1];
    const void* vc = d_in[br * 5 + 2];
    const void* wq = d_in[br * 5 + 3];
    const void* wo = d_in[br * 5 + 4];
    {
      const cuuint64_t dims[2] = {64, (cuuint64_t)2 * kH * kSk * 3};
      const cuuint64_t strides[1] = {128};
      const cuuint32_t box[2] = {64, kTileKeys * 3};
      encode(fn, &p.k[br], kc, 2, dims, strides, box);
      encode(fn, &p.v[br], vc, 2, dims, strides, box);
    }
    {
      const cuuint64_t dims[3] = {64, kHD / 64, kD};
      const cuuint64_t strides[2] = {128, kHD * 2};
      const cuuint32_t box[3] = {64, 3, 64};
      encode(fn, &p.wq[br], wq, 3, dims, strides, box);
    }
    {
      const cuuint64_t dims[2] = {kD, kHD};
      const cuuint64_t strides[1] = {kD * 2};
      const cuuint32_t box[2] = {64, 96};
      encode(fn, &p.wo[br], wo, 2, dims, strides, box);
    }
    p.x[br] = (const __nv_bfloat16*)x;
    p.wq_ptr[br] = (const __nv_bfloat16*)wq;
  }
  p.out = (__nv_bfloat16*)d_out;
  fused_decode_kernel<<<128, kThreads, kSmemBytes>>>(p);
}
```

```cpp
#include <cuda.h>
#include <cuda_bf16.h>
#include <cuda_runtime.h>
#include <stdint.h>

namespace {

constexpr int kD = 640;
constexpr int kH = 32;
constexpr int kSk = 8192;
constexpr int kDh = 192;
constexpr int kHD = kH * kDh;

constexpr int kTileKeys = 64;
constexpr int kSlotBytes = kTileKeys * kDh * 2;
constexpr int kSlots = 9;
constexpr int kKvTiles = kSk / kTileKeys;
constexpr int kWqTiles = 5;
constexpr int kWoTiles = 5;
constexpr int kItems = kWqTiles + 2 * kKvTiles + kWoTiles;
constexpr int kConsWarps = 4;
constexpr int kThreads = (kConsWarps + 1) * 32;
constexpr int kSrcPerBranch = 64;
constexpr int kMTiles = kD / 16;

constexpr int kOffRing = 0;
constexpr int kOffBars = kSlots * kSlotBytes;
constexpr int kOffQPart = kOffBars + 256;
constexpr int kOffRedO = kOffQPart + 2 * kDh * 4;
constexpr int kOffRedML = kOffRedO + 4 * kDh * 4;
constexpr int kOffOBuf = kOffRedML + 32;
constexpr int kOffFin = kOffOBuf + 2 * 48 * 4;
constexpr int kOffTicket = kOffFin + 4 * 32 * 4;
constexpr int kSmemUsed = kOffTicket + 16;
constexpr int kSmemBytes = kSmemUsed + 1024;

constexpr uint32_t kSpinLimit = 1u << 22;
constexpr int kPaceLead = 232;
constexpr int kWoDist = 3;
constexpr int kPaceWrap = 16383;
constexpr int kPacePolls = 512;

struct Params {
  CUtensorMap k[2], v[2], wq[2], wo[2];
  const __nv_bfloat16* x[2];
  const __nv_bfloat16* wq_ptr[2];
  __nv_bfloat16* out;
};

__device__ unsigned long long g_part[2 * kMTiles * kSrcPerBranch * 32];
__device__ unsigned int g_ticket[2 * 32];
__device__ unsigned int g_progress[32];

__device__ __forceinline__ uint32_t smem_u32(const void* p) { return (uint32_t)__cvta_generic_to_shared(p); }

__device__ __forceinline__ void mbar_init(uint32_t bar, uint32_t cnt) {
  asm volatile("mbarrier.init.shared::cta.b64 [%0], %1;" ::"r"(bar), "r"(cnt) : "memory");
}
__device__ __forceinline__ void mbar_expect_tx(uint32_t bar, uint32_t bytes) {
  asm volatile("mbarrier.arrive.expect_tx.shared::cta.b64 _, [%0], %1;" ::"r"(bar), "r"(bytes) : "memory");
}
__device__ __forceinline__ void mbar_arrive(uint32_t bar) {
  asm volatile("mbarrier.arrive.shared::cta.b64 _, [%0];" ::"r"(bar) : "memory");
}
__device__ __forceinline__ bool mbar_try(uint32_t bar, uint32_t parity) {
  uint32_t ok;
  asm volatile(
      "{\n.reg .pred p;\n"
      "mbarrier.try_wait.parity.shared::cta.b64 p, [%1], %2;\n"
      "selp.u32 %0, 1, 0, p;\n}"
      : "=r"(ok)
      : "r"(bar), "r"(parity)
      : "memory");
  return ok != 0;
}
__device__ __forceinline__ bool mbar_try_cluster(uint32_t bar, uint32_t parity) {
  uint32_t ok;
  asm volatile(
      "{\n.reg .pred p;\n"
      "mbarrier.try_wait.parity.acquire.cluster.shared::cta.b64 p, [%1], %2;\n"
      "selp.u32 %0, 1, 0, p;\n}"
      : "=r"(ok)
      : "r"(bar), "r"(parity)
      : "memory");
  return ok != 0;
}
__device__ __forceinline__ void mbar_wait(uint32_t bar, uint32_t parity) {
  uint32_t n = 0;
  while (!mbar_try(bar, parity)) {
    if (++n > kSpinLimit) __trap();
  }
}
__device__ __forceinline__ void mbar_wait_cluster(uint32_t bar, uint32_t parity) {
  uint32_t n = 0;
  while (!mbar_try_cluster(bar, parity)) {
    if (++n > kSpinLimit) __trap();
  }
}

__device__ __forceinline__ void tma_2d(uint32_t dst, const CUtensorMap* tm, int c0, int c1, uint32_t bar,
                                       uint64_t pol) {
  asm volatile(
      "cp.async.bulk.tensor.2d.shared::cluster.global.mbarrier::complete_tx::bytes.L2::cache_hint [%0], [%1, {%3, %4}], "
      "[%2], %5;" ::"r"(dst),
      "l"(tm), "r"(bar), "r"(c0), "r"(c1), "l"(pol)
      : "memory");
}
__device__ __forceinline__ void tma_3d(uint32_t dst, const CUtensorMap* tm, int c0, int c1, int c2, uint32_t bar,
                                       uint64_t pol) {
  asm volatile(
      "cp.async.bulk.tensor.3d.shared::cluster.global.mbarrier::complete_tx::bytes.L2::cache_hint [%0], [%1, {%3, %4, "
      "%5}], [%2], %6;" ::"r"(dst),
      "l"(tm), "r"(bar), "r"(c0), "r"(c1), "r"(c2), "l"(pol)
      : "memory");
}

__device__ __forceinline__ void ldsm4(uint32_t addr, uint32_t (&r)[4]) {
  asm volatile("ldmatrix.sync.aligned.m8n8.x4.shared.b16 {%0,%1,%2,%3}, [%4];"
               : "=r"(r[0]), "=r"(r[1]), "=r"(r[2]), "=r"(r[3])
               : "r"(addr));
}
__device__ __forceinline__ void ldsm4_t(uint32_t addr, uint32_t (&r)[4]) {
  asm volatile("ldmatrix.sync.aligned.m8n8.x4.trans.shared.b16 {%0,%1,%2,%3}, [%4];"
               : "=r"(r[0]), "=r"(r[1]), "=r"(r[2]), "=r"(r[3])
               : "r"(addr));
}
__device__ __forceinline__ void mma_bf16(float (&d)[4], uint32_t a0, uint32_t a1, uint32_t a2, uint32_t a3, uint32_t b0,
                                         uint32_t b1) {
  asm("mma.sync.aligned.m16n8k16.row.col.f32.bf16.bf16.f32 {%0,%1,%2,%3}, {%4,%5,%6,%7}, {%8,%9}, {%0,%1,%2,%3};"
      : "+f"(d[0]), "+f"(d[1]), "+f"(d[2]), "+f"(d[3])
      : "r"(a0), "r"(a1), "r"(a2), "r"(a3), "r"(b0), "r"(b1));
}
__device__ __forceinline__ float ex2(float x) {
  float y;
  asm("ex2.approx.ftz.f32 %0, %1;" : "=f"(y) : "f"(x));
  return y;
}
__device__ __forceinline__ uint32_t pack_bf16(float lo, float hi) {
  uint32_t r;
  asm("cvt.rn.bf16x2.f32 %0, %1, %2;" : "=r"(r) : "f"(hi), "f"(lo));
  return r;
}
__device__ __forceinline__ float bf16_lo(uint32_t v) { return __uint_as_float(v << 16); }
__device__ __forceinline__ float bf16_hi(uint32_t v) { return __uint_as_float(v & 0xffff0000u); }
__device__ __forceinline__ uint32_t mapa(uint32_t addr, uint32_t rank) {
  uint32_t r;
  asm("mapa.shared::cluster.u32 %0, %1, %2;" : "=r"(r) : "r"(addr), "r"(rank));
  return r;
}
__device__ __forceinline__ void st_async_b32(uint32_t addr, uint32_t val, uint32_t bar) {
  asm volatile("st.async.weak.shared::cluster.mbarrier::complete_tx::bytes.b32 [%0], %1, [%2];" ::"r"(addr), "r"(val),
               "r"(bar)
               : "memory");
}
__device__ __forceinline__ float lds_f32(uint32_t addr) {
  float v;
  asm volatile("ld.shared.f32 %0, [%1];" : "=f"(v) : "r"(addr));
  return v;
}
__device__ __forceinline__ uint32_t lds_u32(uint32_t addr) {
  uint32_t v;
  asm volatile("ld.shared.u32 %0, [%1];" : "=r"(v) : "r"(addr));
  return v;
}
__device__ __forceinline__ float2 lds_f32x2(uint32_t addr) {
  float2 v;
  asm volatile("ld.shared.v2.f32 {%0, %1}, [%2];" : "=f"(v.x), "=f"(v.y) : "r"(addr));
  return v;
}
__device__ __forceinline__ void sts_f32(uint32_t addr, float v) {
  asm volatile("st.shared.f32 [%0], %1;" ::"r"(addr), "f"(v) : "memory");
}
__device__ __forceinline__ uint32_t ld_progress() {
  uint32_t v;
  asm volatile("ld.volatile.global.u32 %0, [%1];" : "=r"(v) : "l"(g_progress) : "memory");
  return v;
}
__device__ __forceinline__ void cons_sync() { asm volatile("bar.sync 1, 128;" ::: "memory"); }
__device__ __forceinline__ float sel4(const float (&c)[4], int t) {
  float lo = (t & 1) ? c[1] : c[0];
  float hi = (t & 1) ? c[3] : c[2];
  return (t & 2) ? hi : lo;
}

__global__ void __cluster_dims__(2, 1, 1) __launch_bounds__(kThreads, 1)
    fused_decode_kernel(const __grid_constant__ Params p) {
  extern __shared__ uint8_t smem_raw[];
  const uint32_t sbase = (smem_u32(smem_raw) + 1023u) & ~1023u;
  const uint32_t ring = sbase + kOffRing;
  const uint32_t full0 = sbase + kOffBars;
  const uint32_t empty0 = full0 + 8 * kSlots;
  const uint32_t qbar = empty0 + 8 * kSlots;
  const uint32_t obar = qbar + 8;
  const uint32_t tbar = obar + 8;

  const int warp = threadIdx.x >> 5;
  const int lane = threadIdx.x & 31;
  const int br = blockIdx.x >> 6;
  const int h = (blockIdx.x >> 1) & 31;
  const int b = blockIdx.x & 1;

  if (warp == kConsWarps) {
    const CUtensorMap* tk = &p.k[br];
    const CUtensorMap* tv = &p.v[br];
    const CUtensorMap* twq = &p.wq[br];
    const CUtensorMap* two = &p.wo[br];
    const int kv_row0 = (b * kH + h) * kSk * 3;
    const int tile_rot = (int)(((blockIdx.x + 1) * 2654435761u) >> 20);
    if (lane < 4) {
      const CUtensorMap* tm = lane == 0 ? twq : (lane == 1 ? tk : (lane == 2 ? tv : two));
      asm volatile("prefetch.tensormap [%0];" ::"l"(tm) : "memory");
    }
    if (lane == 0) {
#pragma unroll
      for (int i = 0; i < kSlots; i++) {
        mbar_init(full0 + 8 * i, 1);
        mbar_init(empty0 + 8 * i, kConsWarps);
      }
      mbar_init(qbar, 1);
      mbar_init(obar, 1);
      mbar_init(tbar, 1);
      mbar_expect_tx(qbar, 2 * kDh * 4);
      mbar_expect_tx(obar, 2 * 48 * 4);
      asm volatile("fence.mbarrier_init.release.cluster;" ::: "memory");
      asm volatile("fence.proxy.async.shared::cta;" ::: "memory");
    }
    __syncwarp();
    asm volatile("barrier.cluster.arrive.relaxed.aligned;" ::: "memory");
    uint64_t pol;
    asm volatile("createpolicy.fractional.L2::evict_first.b64 %0, 1.0;" : "=l"(pol));
    auto issue = [&](int item, int slot) {
      const uint32_t dst = ring + slot * kSlotBytes;
      const uint32_t bar = full0 + 8 * slot;
      mbar_expect_tx(bar, kSlotBytes);
      if (item < kWqTiles) {
        tma_3d(dst, twq, 0, h * 3, b * 320 + item * 64, bar, pol);
      } else if (item < kWqTiles + 2 * kKvTiles) {
        const int j = item - kWqTiles;
        tma_2d(dst, (j & 1) ? tv : tk, 0, kv_row0 + (((j >> 1) + tile_rot) & (kKvTiles - 1)) * (kTileKeys * 3), bar, pol);
      } else {
        const int j = item - (kWqTiles + 2 * kKvTiles);
        tma_2d(dst, two, j * 128, h * kDh + b * 96, bar, pol);
        tma_2d(dst + kSlotBytes / 2, two, j * 128 + 64, h * kDh + b * 96, bar, pol);
      }
    };
    if (lane == 0) {
      for (int i = 0; i < kSlots; i++) issue(i, i);
    }
    __syncwarp();
    asm volatile("barrier.cluster.wait.acquire.aligned;" ::: "memory");
    if (lane == 0) {
      int slot = 0;
      uint32_t ph = 0;
      unsigned int ticket = 0;
      unsigned int seen = 0;
      for (int item = kSlots; item < kItems; item++) {
        mbar_wait(empty0 + 8 * slot, ph);
        const int j = item - kWqTiles;
        if (j < 2 * kKvTiles) {
          int polls = 0;
#pragma unroll 1
          while ((int)seen < j * 64 - kPaceLead && polls < kPacePolls) {
            seen = ld_progress();
            polls++;
          }
          issue(item, slot);
          seen = ld_progress();
        } else {
          const int prev = item - kWoDist;
          mbar_wait(full0 + 8 * (prev % kSlots), (prev / kSlots) & 1);
          issue(item, slot);
        }
        if (item == kItems - 24) ticket = atomicAdd(&g_ticket[br * 32], 1u);
        if (item == kItems - 12) {
          asm volatile("st.shared.u32 [%0], %1;" ::"r"(sbase + kOffTicket), "r"(ticket) : "memory");
          mbar_arrive(tbar);
        }
        if (++slot == kSlots) {
          slot = 0;
          ph ^= 1;
        }
      }
    }
  } else {
    const int g = lane >> 2;
    const int t = lane & 3;
    const int mi = lane >> 3;
    const int mr = lane & 7;

    {
      const char* w = reinterpret_cast<const char*>(p.wq_ptr[br] + (size_t)(b * 320) * kHD + h * kDh);
#pragma unroll
      for (int k = 0; k < 2; k++) {
        const int ln = threadIdx.x + 128 * k;
        const int row = ln / 3;
        asm volatile("prefetch.global.L2 [%0];" ::"l"(w + (size_t)row * (kHD * 2) + (ln - row * 3) * 128) : "memory");
      }
    }
    uint32_t xb[20][2];
    {
      const uint32_t* xp = reinterpret_cast<const uint32_t*>(p.x[br] + (g & 1) * kD + b * 320) + t;
#pragma unroll
      for (int kk = 0; kk < 20; kk++) {
        xb[kk][0] = __ldg(xp + kk * 8);
        xb[kk][1] = __ldg(xp + kk * 8 + 4);
      }
    }
    asm volatile("barrier.cluster.arrive.relaxed.aligned;" ::: "memory");
    asm volatile("barrier.cluster.wait.acquire.aligned;" ::: "memory");

    uint32_t off[3];
    {
      const int key = (mi >> 1) * 8 + mr;
#pragma unroll
      for (int j = 0; j < 3; j++) {
        const int R = 3 * key + j;
        off[j] = R * 128 + ((((mi & 1) ^ R) & 7) << 4);
      }
    }

    int slot = 0;
    uint32_t ph = 0;
    auto advance = [&]() {
      if (++slot == kSlots) {
        slot = 0;
        ph ^= 1;
      }
    };
    auto release = [&]() {
      __syncwarp();
      if (lane == 0) mbar_arrive(empty0 + 8 * slot);
    };

    uint32_t qa[12][2];
    {
      float acc[3][4];
      uint32_t woff[3];
#pragma unroll
      for (int u = 0; u < 3; u++) {
        acc[u][0] = acc[u][1] = acc[u][2] = acc[u][3] = 0.f;
        const int s = warp * 3 + u;
        const int j = s >> 2;
        const uint32_t o = j == 0 ? off[0] : (j == 1 ? off[1] : off[2]);
        woff[u] = o ^ ((s & 3) << 5);
      }
#pragma unroll
      for (int it = 0; it < kWqTiles; it++) {
        mbar_wait(full0 + 8 * slot, ph);
        const uint32_t base = ring + slot * kSlotBytes;
        uint32_t a[4][3][4];
#pragma unroll
        for (int ks = 0; ks < 4; ks++)
#pragma unroll
          for (int u = 0; u < 3; u++) ldsm4_t(base + ks * 6144 + woff[u], a[ks][u]);
        release();
        advance();
#pragma unroll
        for (int ks = 0; ks < 4; ks++)
#pragma unroll
          for (int u = 0; u < 3; u++)
            mma_bf16(acc[u], a[ks][u][0], a[ks][u][1], a[ks][u][2], a[ks][u][3], xb[it * 4 + ks][0], xb[it * 4 + ks][1]);
      }
      const uint32_t dst_rank = t & 1;
      const uint32_t dq = mapa(sbase + kOffQPart + b * (kDh * 4), dst_rank);
      const uint32_t dbar = mapa(qbar, dst_rank);
#pragma unroll
      for (int u = 0; u < 3; u++) {
        const int dim = warp * 48 + u * 16 + g + 8 * (t >> 1);
        st_async_b32(dq + dim * 4, __float_as_uint(sel4(acc[u], t)), dbar);
      }
      mbar_wait_cluster(qbar, 0);
#pragma unroll
      for (int s = 0; s < 12; s++) {
#pragma unroll
        for (int hh = 0; hh < 2; hh++) {
          const uint32_t a0 = sbase + kOffQPart + (16 * s + 8 * hh + 2 * t) * 4;
          const float2 u0 = lds_f32x2(a0);
          const float2 u1 = lds_f32x2(a0 + kDh * 4);
          qa[s][hh] = pack_bf16(u0.x + u1.x, u0.y + u1.y);
        }
      }
    }

    constexpr float kScale = 0.07216878364870322f;
    constexpr float kLog2e = 1.4426950408889634f;
    float o[12][4];
#pragma unroll
    for (int s = 0; s < 12; s++) o[s][0] = o[s][1] = o[s][2] = o[s][3] = 0.f;
    float m = -INFINITY, l = 0.f;
    const uint32_t wbase = ring + warp * 6144;

    unsigned long long* const part_dst =
        g_part + ((size_t)(br * kMTiles + 2 * warp) * kSrcPerBranch + (blockIdx.x & 63)) * 32 + lane;

    auto clear_parts = [&]() {
#pragma unroll
      for (int i = 0; i < 2 * kWoTiles; i++)
        asm volatile("st.relaxed.gpu.global.b64 [%0], %1;" ::"l"(part_dst + (size_t)((i >> 1) * 8 + (i & 1)) * (kSrcPerBranch * 32)),
                     "l"(0ull)
                     : "memory");
    };

#pragma unroll 1
    for (int tile = 0; tile < kKvTiles; tile++) {
      uint32_t f[12][4];
      mbar_wait(full0 + 8 * slot, ph);
      {
        const uint32_t base = wbase + slot * kSlotBytes;
#pragma unroll
        for (int s = 0; s < 12; s++) ldsm4((base + off[s >> 2]) ^ ((s & 3) << 5), f[s]);
      }
      release();
      advance();
      float s0[2][4], s1[2][4];
#pragma unroll
      for (int c = 0; c < 2; c++)
#pragma unroll
        for (int e = 0; e < 4; e++) s0[c][e] = s1[c][e] = 0.f;
#pragma unroll
      for (int s = 0; s < 12; s++) {
        mma_bf16(s0[s & 1], qa[s][0], qa[s][0], qa[s][1], qa[s][1], f[s][0], f[s][1]);
        mma_bf16(s1[s & 1], qa[s][0], qa[s][0], qa[s][1], qa[s][1], f[s][2], f[s][3]);
      }
      const uint32_t r01 = pack_bf16(s0[0][0] + s0[1][0], s0[0][1] + s0[1][1]);
      const uint32_t r23 = pack_bf16(s1[0][0] + s1[1][0], s1[0][1] + s1[1][1]);
      const uint32_t t01 = pack_bf16(bf16_lo(r01) * kScale, bf16_hi(r01) * kScale);
      const uint32_t t23 = pack_bf16(bf16_lo(r23) * kScale, bf16_hi(r23) * kScale);
      const float x0 = bf16_lo(t01), x1 = bf16_hi(t01), x2 = bf16_lo(t23), x3 = bf16_hi(t23);
      float mx = fmaxf(fmaxf(x0, x1), fmaxf(x2, x3));
      mx = fmaxf(mx, __shfl_xor_sync(0xffffffffu, mx, 1));
      mx = fmaxf(mx, __shfl_xor_sync(0xffffffffu, mx, 2));
      if (mx > m) {
        const float alpha = ex2((m - mx) * kLog2e);
        m = mx;
        l *= alpha;
#pragma unroll
        for (int s = 0; s < 12; s++) {
          o[s][0] *= alpha;
          o[s][1] *= alpha;
          o[s][2] *= alpha;
          o[s][3] *= alpha;
        }
      }
      const float p0 = ex2((x0 - m) * kLog2e), p1 = ex2((x1 - m) * kLog2e);
      const float p2 = ex2((x2 - m) * kLog2e), p3 = ex2((x3 - m) * kLog2e);
      l += (p0 + p1) + (p2 + p3);
      const uint32_t pb0 = pack_bf16(p0, p1), pb1 = pack_bf16(p2, p3);

      mbar_wait(full0 + 8 * slot, ph);
      {
        const uint32_t base = wbase + slot * kSlotBytes;
#pragma unroll
        for (int s = 0; s < 12; s++) ldsm4_t((base + off[s >> 2]) ^ ((s & 3) << 5), f[s]);
      }
      release();
      advance();
      if (threadIdx.x == 0) asm volatile("red.relaxed.gpu.global.inc.u32 [%0], %1;" ::"l"(g_progress), "n"(kPaceWrap) : "memory");
#pragma unroll
      for (int s = 0; s < 12; s++) mma_bf16(o[s], f[s][0], f[s][1], f[s][2], f[s][3], pb0, pb1);
    }
    clear_parts();

    l += __shfl_xor_sync(0xffffffffu, l, 1);
    l += __shfl_xor_sync(0xffffffffu, l, 2);
#pragma unroll
    for (int s = 0; s < 12; s++) {
      if ((s & 3) == t) {
        sts_f32(sbase + kOffRedO + (warp * kDh + s * 16 + g) * 4, o[s][0]);
        sts_f32(sbase + kOffRedO + (warp * kDh + s * 16 + 8 + g) * 4, o[s][2]);
      }
    }
    if (lane == 0) {
      sts_f32(sbase + kOffRedML + warp * 4, m);
      sts_f32(sbase + kOffRedML + 16 + warp * 4, l);
    }
    cons_sync();
    if (threadIdx.x < 96) {
      float mw[4], lw[4];
#pragma unroll
      for (int w = 0; w < 4; w++) {
        mw[w] = lds_f32(sbase + kOffRedML + w * 4);
        lw[w] = lds_f32(sbase + kOffRedML + 16 + w * 4);
      }
      const float mm = fmaxf(fmaxf(mw[0], mw[1]), fmaxf(mw[2], mw[3]));
      float L = 0.f, ox = 0.f, oy = 0.f;
#pragma unroll
      for (int w = 0; w < 4; w++) {
        const float a = ex2((mw[w] - mm) * kLog2e);
        const float2 v = lds_f32x2(sbase + kOffRedO + (w * kDh + 2 * threadIdx.x) * 4);
        L = fmaf(lw[w], a, L);
        ox = fmaf(v.x, a, ox);
        oy = fmaf(v.y, a, oy);
      }
      const float inv = 1.0f / L;
      const uint32_t dst_rank = threadIdx.x >= 48;
      const uint32_t idx = threadIdx.x - 48 * dst_rank;
      st_async_b32(mapa(sbase + kOffOBuf + (b * 48 + idx) * 4, dst_rank), pack_bf16(ox * inv, oy * inv),
                   mapa(obar, dst_rank));
    }
    mbar_wait_cluster(obar, 0);
    uint32_t ob[6][2];
#pragma unroll
    for (int ks = 0; ks < 6; ks++) {
      ob[ks][0] = lds_u32(sbase + kOffOBuf + ((g & 1) * 48 + ks * 8 + t) * 4);
      ob[ks][1] = lds_u32(sbase + kOffOBuf + ((g & 1) * 48 + ks * 8 + 4 + t) * 4);
    }
    mbar_wait(tbar, 0);
    const uint32_t ticket = lds_u32(sbase + kOffTicket);
    const uint32_t tag = (ticket >> 6) + 1;
    const int rank = ticket & 63;

    {
      const uint32_t wo_off = (warp >> 1) * 12288 + ((mi >> 1) * 8 + mr) * 128;
      const uint32_t ch0 = ((4 * (warp & 1) + (mi & 1)) ^ mr) << 4;
      unsigned long long* const dst = part_dst;
#pragma unroll 1
      for (int it = 0; it < kWoTiles; it++) {
        mbar_wait(full0 + 8 * slot, ph);
        const uint32_t base = ring + slot * kSlotBytes + wo_off;
        uint32_t a[2][6][4];
#pragma unroll
        for (int u = 0; u < 2; u++)
#pragma unroll
          for (int ks = 0; ks < 6; ks++) ldsm4_t(base + ks * 2048 + (ch0 ^ (u << 5)), a[u][ks]);
        advance();
#pragma unroll
        for (int u = 0; u < 2; u++) {
          float acc0[4] = {0.f, 0.f, 0.f, 0.f}, acc1[4] = {0.f, 0.f, 0.f, 0.f};
#pragma unroll
          for (int ks = 0; ks < 6; ks += 2) {
            mma_bf16(acc0, a[u][ks][0], a[u][ks][1], a[u][ks][2], a[u][ks][3], ob[ks][0], ob[ks][1]);
            mma_bf16(acc1, a[u][ks + 1][0], a[u][ks + 1][1], a[u][ks + 1][2], a[u][ks + 1][3], ob[ks + 1][0],
                     ob[ks + 1][1]);
          }
          const float v = sel4(acc0, t) + sel4(acc1, t);
          const unsigned long long w = ((unsigned long long)tag << 32) | __float_as_uint(v);
          asm volatile("st.relaxed.gpu.global.b64 [%0], %1;" ::"l"(dst + (size_t)(it * 8 + u) * (kSrcPerBranch * 32)),
                       "l"(w)
                       : "memory");
        }
      }
    }

    if (rank >= kSrcPerBranch - kMTiles) {
      const int mt = rank - (kSrcPerBranch - kMTiles);
      const unsigned long long* srcp = g_part + ((size_t)(br * kMTiles + mt) * kSrcPerBranch + warp * 16) * 32 + lane;
      unsigned long long w[16];
#pragma unroll
      for (int j = 0; j < 16; j++) w[j] = 0;
      uint32_t spins = 0;
      while (true) {
        bool ok = true;
#pragma unroll
        for (int j = 0; j < 16; j++) {
          if ((uint32_t)(w[j] >> 32) != tag)
            asm volatile("ld.relaxed.gpu.global.b64 %0, [%1];" : "=l"(w[j]) : "l"(srcp + j * 32) : "memory");
        }
#pragma unroll
        for (int j = 0; j < 16; j++) ok = ok && ((uint32_t)(w[j] >> 32) == tag);
        if (ok) break;
        if (++spins > kSpinLimit) __trap();
      }
      float v = 0.f;
#pragma unroll
      for (int j = 0; j < 16; j++) v += __uint_as_float((uint32_t)w[j]);
      sts_f32(sbase + kOffFin + (warp * 32 + lane) * 4, v);
      cons_sync();
      if (warp == 0) {
        float r = 0.f;
#pragma unroll
        for (int ww = 0; ww < 4; ww++) r += lds_f32(sbase + kOffFin + (ww * 32 + lane) * 4);
        const int col = mt * 16 + g + 8 * (t >> 1);
        p.out[(t & 1) * (2 * kD) + br * kD + col] = __float2bfloat16_rn(r);
      }
    }
  }
}

typedef CUresult (*EncodeTiledFn)(CUtensorMap*, CUtensorMapDataType, cuuint32_t, void*, const cuuint64_t*,
                                  const cuuint64_t*, const cuuint32_t*, const cuuint32_t*, CUtensorMapInterleave,
                                  CUtensorMapSwizzle, CUtensorMapL2promotion, CUtensorMapFloatOOBfill);

void encode(EncodeTiledFn fn, CUtensorMap* m, const void* base, int rank, const cuuint64_t* dims,
            const cuuint64_t* strides, const cuuint32_t* box) {
  const cuuint32_t es[3] = {1, 1, 1};
  fn(m, CU_TENSOR_MAP_DATA_TYPE_BFLOAT16, rank, const_cast<void*>(base), dims, strides, box, es,
     CU_TENSOR_MAP_INTERLEAVE_NONE, CU_TENSOR_MAP_SWIZZLE_128B, CU_TENSOR_MAP_L2_PROMOTION_NONE,
     CU_TENSOR_MAP_FLOAT_OOB_FILL_NONE);
}

}

extern "C" void kernel_launch(void* const* d_in, const int* in_sizes, int n_in, void* d_out, int out_size) {
  (void)in_sizes;
  (void)n_in;
  (void)out_size;
  static EncodeTiledFn fn = nullptr;
  if (!fn) {
    void* sym = nullptr;
    cudaDriverEntryPointQueryResult qr;
    cudaGetDriverEntryPoint("cuTensorMapEncodeTiled", &sym, cudaEnableDefault, &qr);
    fn = (EncodeTiledFn)sym;
    cudaFuncSetAttribute(fused_decode_kernel, cudaFuncAttributeMaxDynamicSharedMemorySize, kSmemBytes);
  }
  Params p;
  for (int br = 0; br < 2; br++) {
    const void* x = d_in[br * 5 + 0];
    const void* kc = d_in[br * 5 + 1];
    const void* vc = d_in[br * 5 + 2];
    const void* wq = d_in[br * 5 + 3];
    const void* wo = d_in[br * 5 + 4];
    {
      const cuuint64_t dims[2] = {64, (cuuint64_t)2 * kH * kSk * 3};
      const cuuint64_t strides[1] = {128};
      const cuuint32_t box[2] = {64, kTileKeys * 3};
      encode(fn, &p.k[br], kc, 2, dims, strides, box);
      encode(fn, &p.v[br], vc, 2, dims, strides, box);
    }
    {
      const cuuint64_t dims[3] = {64, kHD / 64, kD};
      const cuuint64_t strides[2] = {128, kHD * 2};
      const cuuint32_t box[3] = {64, 3, 64};
      encode(fn, &p.wq[br], wq, 3, dims, strides, box);
    }
    {
      const cuuint64_t dims[2] = {kD, kHD};
      const cuuint64_t strides[1] = {kD * 2};
      const cuuint32_t box[2] = {64, 96};
      encode(fn, &p.wo[br], wo, 2, dims, strides, box);
    }
    p.x[br] = (const __nv_bfloat16*)x;
    p.wq_ptr[br] = (const __nv_bfloat16*)wq;
  }
  p.out = (__nv_bfloat16*)d_out;
  fused_decode_kernel<<<128, kThreads, kSmemBytes>>>(p);
}
```

```cpp
#include <cuda.h>
#include <cuda_bf16.h>
#include <cuda_runtime.h>
#include <stdint.h>

namespace {

constexpr int kD = 640;
constexpr int kH = 32;
constexpr int kSk = 8192;
constexpr int kDh = 192;
constexpr int kHD = kH * kDh;

constexpr int kTileKeys = 64;
constexpr int kSlotBytes = kTileKeys * kDh * 2;
constexpr int kSlots = 9;
constexpr int kKvTiles = kSk / kTileKeys;
constexpr int kWqTiles = 5;
constexpr int kWoTiles = 5;
constexpr int kItems = kWqTiles + 2 * kKvTiles + kWoTiles;
constexpr int kConsWarps = 4;
constexpr int kThreads = (kConsWarps + 1) * 32;
constexpr int kSrcPerBranch = 64;
constexpr int kMTiles = kD / 16;

constexpr int kOffRing = 0;
constexpr int kOffBars = kSlots * kSlotBytes;
constexpr int kOffQPart = kOffBars + 256;
constexpr int kOffRedO = kOffQPart + 2 * kDh * 4;
constexpr int kOffRedML = kOffRedO + 4 * kDh * 4;
constexpr int kOffOBuf = kOffRedML + 32;
constexpr int kOffFin = kOffOBuf + 2 * 48 * 4;
constexpr int kOffTicket = kOffFin + 4 * 32 * 4;
constexpr int kSmemUsed = kOffTicket + 16;
constexpr int kSmemBytes = kSmemUsed + 1024;

constexpr uint32_t kSpinLimit = 1u << 22;
constexpr int kPaceLead = 232;
constexpr int kWoDist = 3;
constexpr int kPaceWrap = 16383;
constexpr int kPacePolls = 512;

struct Params {
  CUtensorMap k[2], v[2], wq[2], wo[2];
  const __nv_bfloat16* x[2];
  const __nv_bfloat16* wq_ptr[2];
  __nv_bfloat16* out;
};

__device__ unsigned long long g_part[2 * kMTiles * kSrcPerBranch * 32];
__device__ unsigned int g_ticket[2 * 32];
__device__ unsigned int g_progress[32];

__device__ __forceinline__ uint32_t smem_u32(const void* p) { return (uint32_t)__cvta_generic_to_shared(p); }

__device__ __forceinline__ void mbar_init(uint32_t bar, uint32_t cnt) {
  asm volatile("mbarrier.init.shared::cta.b64 [%0], %1;" ::"r"(bar), "r"(cnt) : "memory");
}
__device__ __forceinline__ void mbar_expect_tx(uint32_t bar, uint32_t bytes) {
  asm volatile("mbarrier.arrive.expect_tx.shared::cta.b64 _, [%0], %1;" ::"r"(bar), "r"(bytes) : "memory");
}
__device__ __forceinline__ void mbar_arrive(uint32_t bar) {
  asm volatile("mbarrier.arrive.shared::cta.b64 _, [%0];" ::"r"(bar) : "memory");
}
__device__ __forceinline__ bool mbar_try(uint32_t bar, uint32_t parity) {
  uint32_t ok;
  asm volatile(
      "{\n.reg .pred p;\n"
      "mbarrier.try_wait.parity.shared::cta.b64 p, [%1], %2;\n"
      "selp.u32 %0, 1, 0, p;\n}"
      : "=r"(ok)
      : "r"(bar), "r"(parity)
      : "memory");
  return ok != 0;
}
__device__ __forceinline__ bool mbar_try_cluster(uint32_t bar, uint32_t parity) {
  uint32_t ok;
  asm volatile(
      "{\n.reg .pred p;\n"
      "mbarrier.try_wait.parity.acquire.cluster.shared::cta.b64 p, [%1], %2;\n"
      "selp.u32 %0, 1, 0, p;\n}"
      : "=r"(ok)
      : "r"(bar), "r"(parity)
      : "memory");
  return ok != 0;
}
__device__ __forceinline__ void mbar_wait(uint32_t bar, uint32_t parity) {
  uint32_t n = 0;
  while (!mbar_try(bar, parity)) {
    if (++n > kSpinLimit) __trap();
  }
}
__device__ __forceinline__ void mbar_wait_cluster(uint32_t bar, uint32_t parity) {
  uint32_t n = 0;
  while (!mbar_try_cluster(bar, parity)) {
    if (++n > kSpinLimit) __trap();
  }
}

__device__ __forceinline__ void tma_2d(uint32_t dst, const CUtensorMap* tm, int c0, int c1, uint32_t bar,
                                       uint64_t pol) {
  asm volatile(
      "cp.async.bulk.tensor.2d.shared::cluster.global.mbarrier::complete_tx::bytes.L2::cache_hint [%0], [%1, {%3, %4}], "
      "[%2], %5;" ::"r"(dst),
      "l"(tm), "r"(bar), "r"(c0), "r"(c1), "l"(pol)
      : "memory");
}
__device__ __forceinline__ void tma_3d(uint32_t dst, const CUtensorMap* tm, int c0, int c1, int c2, uint32_t bar,
                                       uint64_t pol) {
  asm volatile(
      "cp.async.bulk.tensor.3d.shared::cluster.global.mbarrier::complete_tx::bytes.L2::cache_hint [%0], [%1, {%3, %4, "
      "%5}], [%2], %6;" ::"r"(dst),
      "l"(tm), "r"(bar), "r"(c0), "r"(c1), "r"(c2), "l"(pol)
      : "memory");
}

__device__ __forceinline__ void ldsm4(uint32_t addr, uint32_t (&r)[4]) {
  asm volatile("ldmatrix.sync.aligned.m8n8.x4.shared.b16 {%0,%1,%2,%3}, [%4];"
               : "=r"(r[0]), "=r"(r[1]), "=r"(r[2]), "=r"(r[3])
               : "r"(addr));
}
__device__ __forceinline__ void ldsm4_t(uint32_t addr, uint32_t (&r)[4]) {
  asm volatile("ldmatrix.sync.aligned.m8n8.x4.trans.shared.b16 {%0,%1,%2,%3}, [%4];"
               : "=r"(r[0]), "=r"(r[1]), "=r"(r[2]), "=r"(r[3])
               : "r"(addr));
}
__device__ __forceinline__ void mma_bf16(float (&d)[4], uint32_t a0, uint32_t a1, uint32_t a2, uint32_t a3, uint32_t b0,
                                         uint32_t b1) {
  asm("mma.sync.aligned.m16n8k16.row.col.f32.bf16.bf16.f32 {%0,%1,%2,%3}, {%4,%5,%6,%7}, {%8,%9}, {%0,%1,%2,%3};"
      : "+f"(d[0]), "+f"(d[1]), "+f"(d[2]), "+f"(d[3])
      : "r"(a0), "r"(a1), "r"(a2), "r"(a3), "r"(b0), "r"(b1));
}
__device__ __forceinline__ float ex2(float x) {
  float y;
  asm("ex2.approx.ftz.f32 %0, %1;" : "=f"(y) : "f"(x));
  return y;
}
__device__ __forceinline__ uint32_t pack_bf16(float lo, float hi) {
  uint32_t r;
  asm("cvt.rn.bf16x2.f32 %0, %1, %2;" : "=r"(r) : "f"(hi), "f"(lo));
  return r;
}
__device__ __forceinline__ float bf16_lo(uint32_t v) { return __uint_as_float(v << 16); }
__device__ __forceinline__ float bf16_hi(uint32_t v) { return __uint_as_float(v & 0xffff0000u); }
__device__ __forceinline__ uint32_t mapa(uint32_t addr, uint32_t rank) {
  uint32_t r;
  asm("mapa.shared::cluster.u32 %0, %1, %2;" : "=r"(r) : "r"(addr), "r"(rank));
  return r;
}
__device__ __forceinline__ void st_async_b32(uint32_t addr, uint32_t val, uint32_t bar) {
  asm volatile("st.async.weak.shared::cluster.mbarrier::complete_tx::bytes.b32 [%0], %1, [%2];" ::"r"(addr), "r"(val),
               "r"(bar)
               : "memory");
}
__device__ __forceinline__ float lds_f32(uint32_t addr) {
  float v;
  asm volatile("ld.shared.f32 %0, [%1];" : "=f"(v) : "r"(addr));
  return v;
}
__device__ __forceinline__ uint32_t lds_u32(uint32_t addr) {
  uint32_t v;
  asm volatile("ld.shared.u32 %0, [%1];" : "=r"(v) : "r"(addr));
  return v;
}
__device__ __forceinline__ float2 lds_f32x2(uint32_t addr) {
  float2 v;
  asm volatile("ld.shared.v2.f32 {%0, %1}, [%2];" : "=f"(v.x), "=f"(v.y) : "r"(addr));
  return v;
}
__device__ __forceinline__ void sts_f32(uint32_t addr, float v) {
  asm volatile("st.shared.f32 [%0], %1;" ::"r"(addr), "f"(v) : "memory");
}
__device__ __forceinline__ uint32_t ld_progress() {
  uint32_t v;
  asm volatile("ld.volatile.global.u32 %0, [%1];" : "=r"(v) : "l"(g_progress) : "memory");
  return v;
}
__device__ __forceinline__ void cons_sync() { asm volatile("bar.sync 1, 128;" ::: "memory"); }
__device__ __forceinline__ float sel4(const float (&c)[4], int t) {
  float lo = (t & 1) ? c[1] : c[0];
  float hi = (t & 1) ? c[3] : c[2];
  return (t & 2) ? hi : lo;
}

__global__ void __cluster_dims__(2, 1, 1) __launch_bounds__(kThreads, 1)
    fused_decode_kernel(const __grid_constant__ Params p) {
  extern __shared__ uint8_t smem_raw[];
  const uint32_t sbase = (smem_u32(smem_raw) + 1023u) & ~1023u;
  const uint32_t ring = sbase + kOffRing;
  const uint32_t full0 = sbase + kOffBars;
  const uint32_t empty0 = full0 + 8 * kSlots;
  const uint32_t qbar = empty0 + 8 * kSlots;
  const uint32_t obar = qbar + 8;
  const uint32_t tbar = obar + 8;

  const int warp = threadIdx.x >> 5;
  const int lane = threadIdx.x & 31;
  const int br = blockIdx.x >> 6;
  const int h = (blockIdx.x >> 1) & 31;
  const int b = blockIdx.x & 1;

  if (warp == kConsWarps) {
    const CUtensorMap* tk = &p.k[br];
    const CUtensorMap* tv = &p.v[br];
    const CUtensorMap* twq = &p.wq[br];
    const CUtensorMap* two = &p.wo[br];
    const int kv_row0 = (b * kH + h) * kSk * 3;
    const int tile_rot = (int)(((blockIdx.x + 1) * 2654435761u) >> 20);
    if (lane < 4) {
      const CUtensorMap* tm = lane == 0 ? twq : (lane == 1 ? tk : (lane == 2 ? tv : two));
      asm volatile("prefetch.tensormap [%0];" ::"l"(tm) : "memory");
    }
    if (lane == 0) {
#pragma unroll
      for (int i = 0; i < kSlots; i++) {
        mbar_init(full0 + 8 * i, 1);
        mbar_init(empty0 + 8 * i, kConsWarps);
      }
      mbar_init(qbar, 1);
      mbar_init(obar, 1);
      mbar_init(tbar, 1);
      mbar_expect_tx(qbar, 2 * kDh * 4);
      mbar_expect_tx(obar, 2 * 48 * 4);
      asm volatile("fence.mbarrier_init.release.cluster;" ::: "memory");
      asm volatile("fence.proxy.async.shared::cta;" ::: "memory");
    }
    __syncwarp();
    asm volatile("barrier.cluster.arrive.relaxed.aligned;" ::: "memory");
    uint64_t pol;
    asm volatile("createpolicy.fractional.L2::evict_first.b64 %0, 1.0;" : "=l"(pol));
    auto issue = [&](int item, int slot) {
      const uint32_t dst = ring + slot * kSlotBytes;
      const uint32_t bar = full0 + 8 * slot;
      mbar_expect_tx(bar, kSlotBytes);
      if (item < kWqTiles) {
        tma_3d(dst, twq, 0, h * 3, b * 320 + item * 64, bar, pol);
      } else if (item < kWqTiles + 2 * kKvTiles) {
        const int j = item - kWqTiles;
        tma_2d(dst, (j & 1) ? tv : tk, 0, kv_row0 + (((j >> 1) + tile_rot) & (kKvTiles - 1)) * (kTileKeys * 3), bar, pol);
      } else {
        const int j = item - (kWqTiles + 2 * kKvTiles);
        tma_2d(dst, two, j * 128, h * kDh + b * 96, bar, pol);
        tma_2d(dst + kSlotBytes / 2, two, j * 128 + 64, h * kDh + b * 96, bar, pol);
      }
    };
    if (lane == 0) {
      for (int i = 0; i < kSlots; i++) issue(i, i);
    }
    __syncwarp();
    asm volatile("barrier.cluster.wait.acquire.aligned;" ::: "memory");
    if (lane == 0) {
      int slot = 0;
      uint32_t ph = 0;
      unsigned int ticket = 0;
      unsigned int seen = 0;
      for (int item = kSlots; item < kItems; item++) {
        mbar_wait(empty0 + 8 * slot, ph);
        const int j = item - kWqTiles;
        if (j < 2 * kKvTiles) {
          int polls = 0;
#pragma unroll 1
          while ((int)seen < j * 64 - kPaceLead && polls < kPacePolls) {
            seen = ld_progress();
            polls++;
          }
          issue(item, slot);
          seen = ld_progress();
        } else {
          const int prev = item - kWoDist;
          mbar_wait(full0 + 8 * (prev % kSlots), (prev / kSlots) & 1);
          issue(item, slot);
        }
        if (item == kItems - 24) ticket = atomicAdd(&g_ticket[br * 32], 1u);
        if (item == kItems - 12) {
          asm volatile("st.shared.u32 [%0], %1;" ::"r"(sbase + kOffTicket), "r"(ticket) : "memory");
          mbar_arrive(tbar);
        }
        if (++slot == kSlots) {
          slot = 0;
          ph ^= 1;
        }
      }
    }
  } else {
    const int g = lane >> 2;
    const int t = lane & 3;
    const int mi = lane >> 3;
    const int mr = lane & 7;

    if (threadIdx.x < 96) {
      const int row = threadIdx.x / 3;
      const char* w = reinterpret_cast<const char*>(p.wq_ptr[br] + (size_t)(b * 320 + row) * kHD + h * kDh);
      asm volatile("prefetch.global.L2 [%0];" ::"l"(w + (threadIdx.x - row * 3) * 128) : "memory");
    }
    asm volatile("barrier.cluster.arrive.relaxed.aligned;" ::: "memory");
    asm volatile("barrier.cluster.wait.acquire.aligned;" ::: "memory");

    uint32_t xb[20][2];
    {
      const uint32_t* xp = reinterpret_cast<const uint32_t*>(p.x[br] + (g & 1) * kD + b * 320) + t;
#pragma unroll
      for (int kk = 0; kk < 20; kk++) {
        xb[kk][0] = __ldg(xp + kk * 8);
        xb[kk][1] = __ldg(xp + kk * 8 + 4);
      }
    }

    uint32_t off[3];
    {
      const int key = (mi >> 1) * 8 + mr;
#pragma unroll
      for (int j = 0; j < 3; j++) {
        const int R = 3 * key + j;
        off[j] = R * 128 + ((((mi & 1) ^ R) & 7) << 4);
      }
    }

    int slot = 0;
    uint32_t ph = 0;
    auto advance = [&]() {
      if (++slot == kSlots) {
        slot = 0;
        ph ^= 1;
      }
    };
    auto release = [&]() {
      __syncwarp();
      if (lane == 0) mbar_arrive(empty0 + 8 * slot);
    };

    uint32_t qa[12][2];
    {
      float acc[3][4];
      uint32_t woff[3];
#pragma unroll
      for (int u = 0; u < 3; u++) {
        acc[u][0] = acc[u][1] = acc[u][2] = acc[u][3] = 0.f;
        const int s = warp * 3 + u;
        const int j = s >> 2;
        const uint32_t o = j == 0 ? off[0] : (j == 1 ? off[1] : off[2]);
        woff[u] = o ^ ((s & 3) << 5);
      }
#pragma unroll
      for (int it = 0; it < kWqTiles; it++) {
        mbar_wait(full0 + 8 * slot, ph);
        const uint32_t base = ring + slot * kSlotBytes;
        uint32_t a[4][3][4];
#pragma unroll
        for (int ks = 0; ks < 4; ks++)
#pragma unroll
          for (int u = 0; u < 3; u++) ldsm4_t(base + ks * 6144 + woff[u], a[ks][u]);
        release();
        advance();
#pragma unroll
        for (int ks = 0; ks < 4; ks++)
#pragma unroll
          for (int u = 0; u < 3; u++)
            mma_bf16(acc[u], a[ks][u][0], a[ks][u][1], a[ks][u][2], a[ks][u][3], xb[it * 4 + ks][0], xb[it * 4 + ks][1]);
      }
      const uint32_t dst_rank = t & 1;
      const uint32_t dq = mapa(sbase + kOffQPart + b * (kDh * 4), dst_rank);
      const uint32_t dbar = mapa(qbar, dst_rank);
#pragma unroll
      for (int u = 0; u < 3; u++) {
        const int dim = warp * 48 + u * 16 + g + 8 * (t >> 1);
        st_async_b32(dq + dim * 4, __float_as_uint(sel4(acc[u], t)), dbar);
      }
      mbar_wait_cluster(qbar, 0);
#pragma unroll
      for (int s = 0; s < 12; s++) {
#pragma unroll
        for (int hh = 0; hh < 2; hh++) {
          const uint32_t a0 = sbase + kOffQPart + (16 * s + 8 * hh + 2 * t) * 4;
          const float2 u0 = lds_f32x2(a0);
          const float2 u1 = lds_f32x2(a0 + kDh * 4);
          qa[s][hh] = pack_bf16(u0.x + u1.x, u0.y + u1.y);
        }
      }
    }

    constexpr float kScale = 0.07216878364870322f;
    constexpr float kLog2e = 1.4426950408889634f;
    float o[12][4];
#pragma unroll
    for (int s = 0; s < 12; s++) o[s][0] = o[s][1] = o[s][2] = o[s][3] = 0.f;
    float m = -INFINITY, l = 0.f;
    const uint32_t wbase = ring + warp * 6144;

    unsigned long long* const part_dst =
        g_part + ((size_t)(br * kMTiles + 2 * warp) * kSrcPerBranch + (blockIdx.x & 63)) * 32 + lane;

    auto clear_parts = [&]() {
#pragma unroll
      for (int i = 0; i < 2 * kWoTiles; i++)
        asm volatile("st.relaxed.gpu.global.b64 [%0], %1;" ::"l"(part_dst + (size_t)((i >> 1) * 8 + (i & 1)) * (kSrcPerBranch * 32)),
                     "l"(0ull)
                     : "memory");
    };

#pragma unroll 1
    for (int tile = 0; tile < kKvTiles; tile++) {
      uint32_t f[12][4];
      mbar_wait(full0 + 8 * slot, ph);
      {
        const uint32_t base = wbase + slot * kSlotBytes;
#pragma unroll
        for (int s = 0; s < 12; s++) ldsm4((base + off[s >> 2]) ^ ((s & 3) << 5), f[s]);
      }
      release();
      advance();
      float s0[2][4], s1[2][4];
#pragma unroll
      for (int c = 0; c < 2; c++)
#pragma unroll
        for (int e = 0; e < 4; e++) s0[c][e] = s1[c][e] = 0.f;
#pragma unroll
      for (int s = 0; s < 12; s++) {
        mma_bf16(s0[s & 1], qa[s][0], qa[s][0], qa[s][1], qa[s][1], f[s][0], f[s][1]);
        mma_bf16(s1[s & 1], qa[s][0], qa[s][0], qa[s][1], qa[s][1], f[s][2], f[s][3]);
      }
      const uint32_t r01 = pack_bf16(s0[0][0] + s0[1][0], s0[0][1] + s0[1][1]);
      const uint32_t r23 = pack_bf16(s1[0][0] + s1[1][0], s1[0][1] + s1[1][1]);
      const uint32_t t01 = pack_bf16(bf16_lo(r01) * kScale, bf16_hi(r01) * kScale);
      const uint32_t t23 = pack_bf16(bf16_lo(r23) * kScale, bf16_hi(r23) * kScale);
      const float x0 = bf16_lo(t01), x1 = bf16_hi(t01), x2 = bf16_lo(t23), x3 = bf16_hi(t23);
      float mx = fmaxf(fmaxf(x0, x1), fmaxf(x2, x3));
      mx = fmaxf(mx, __shfl_xor_sync(0xffffffffu, mx, 1));
      mx = fmaxf(mx, __shfl_xor_sync(0xffffffffu, mx, 2));
      if (mx > m) {
        const float alpha = ex2((m - mx) * kLog2e);
        m = mx;
        l *= alpha;
#pragma unroll
        for (int s = 0; s < 12; s++) {
          o[s][0] *= alpha;
          o[s][1] *= alpha;
          o[s][2] *= alpha;
          o[s][3] *= alpha;
        }
      }
      const float p0 = ex2((x0 - m) * kLog2e), p1 = ex2((x1 - m) * kLog2e);
      const float p2 = ex2((x2 - m) * kLog2e), p3 = ex2((x3 - m) * kLog2e);
      l += (p0 + p1) + (p2 + p3);
      const uint32_t pb0 = pack_bf16(p0, p1), pb1 = pack_bf16(p2, p3);

      mbar_wait(full0 + 8 * slot, ph);
      {
        const uint32_t base = wbase + slot * kSlotBytes;
#pragma unroll
        for (int s = 0; s < 12; s++) ldsm4_t((base + off[s >> 2]) ^ ((s & 3) << 5), f[s]);
      }
      release();
      advance();
      if (threadIdx.x == 0) asm volatile("red.relaxed.gpu.global.inc.u32 [%0], %1;" ::"l"(g_progress), "n"(kPaceWrap) : "memory");
#pragma unroll
      for (int s = 0; s < 12; s++) mma_bf16(o[s], f[s][0], f[s][1], f[s][2], f[s][3], pb0, pb1);
    }
    clear_parts();

    l += __shfl_xor_sync(0xffffffffu, l, 1);
    l += __shfl_xor_sync(0xffffffffu, l, 2);
#pragma unroll
    for (int s = 0; s < 12; s++) {
      if ((s & 3) == t) {
        sts_f32(sbase + kOffRedO + (warp * kDh + s * 16 + g) * 4, o[s][0]);
        sts_f32(sbase + kOffRedO + (warp * kDh + s * 16 + 8 + g) * 4, o[s][2]);
      }
    }
    if (lane == 0) {
      sts_f32(sbase + kOffRedML + warp * 4, m);
      sts_f32(sbase + kOffRedML + 16 + warp * 4, l);
    }
    cons_sync();
    if (threadIdx.x < 96) {
      float mw[4], lw[4];
#pragma unroll
      for (int w = 0; w < 4; w++) {
        mw[w] = lds_f32(sbase + kOffRedML + w * 4);
        lw[w] = lds_f32(sbase + kOffRedML + 16 + w * 4);
      }
      const float mm = fmaxf(fmaxf(mw[0], mw[1]), fmaxf(mw[2], mw[3]));
      float L = 0.f, ox = 0.f, oy = 0.f;
#pragma unroll
      for (int w = 0; w < 4; w++) {
        const float a = ex2((mw[w] - mm) * kLog2e);
        const float2 v = lds_f32x2(sbase + kOffRedO + (w * kDh + 2 * threadIdx.x) * 4);
        L = fmaf(lw[w], a, L);
        ox = fmaf(v.x, a, ox);
        oy = fmaf(v.y, a, oy);
      }
      const float inv = 1.0f / L;
      const uint32_t dst_rank = threadIdx.x >= 48;
      const uint32_t idx = threadIdx.x - 48 * dst_rank;
      st_async_b32(mapa(sbase + kOffOBuf + (b * 48 + idx) * 4, dst_rank), pack_bf16(ox * inv, oy * inv),
                   mapa(obar, dst_rank));
    }
    mbar_wait_cluster(obar, 0);
    uint32_t ob[6][2];
#pragma unroll
    for (int ks = 0; ks < 6; ks++) {
      ob[ks][0] = lds_u32(sbase + kOffOBuf + ((g & 1) * 48 + ks * 8 + t) * 4);
      ob[ks][1] = lds_u32(sbase + kOffOBuf + ((g & 1) * 48 + ks * 8 + 4 + t) * 4);
    }
    mbar_wait(tbar, 0);
    const uint32_t ticket = lds_u32(sbase + kOffTicket);
    const uint32_t tag = (ticket >> 6) + 1;
    const int rank = ticket & 63;

    {
      const uint32_t wo_off = (warp >> 1) * 12288 + ((mi >> 1) * 8 + mr) * 128;
      const uint32_t ch0 = ((4 * (warp & 1) + (mi & 1)) ^ mr) << 4;
      unsigned long long* const dst = part_dst;
#pragma unroll 1
      for (int it = 0; it < kWoTiles; it++) {
        mbar_wait(full0 + 8 * slot, ph);
        const uint32_t base = ring + slot * kSlotBytes + wo_off;
        uint32_t a[2][6][4];
#pragma unroll
        for (int u = 0; u < 2; u++)
#pragma unroll
          for (int ks = 0; ks < 6; ks++) ldsm4_t(base + ks * 2048 + (ch0 ^ (u << 5)), a[u][ks]);
        advance();
#pragma unroll
        for (int u = 0; u < 2; u++) {
          float acc0[4] = {0.f, 0.f, 0.f, 0.f}, acc1[4] = {0.f, 0.f, 0.f, 0.f};
#pragma unroll
          for (int ks = 0; ks < 6; ks += 2) {
            mma_bf16(acc0, a[u][ks][0], a[u][ks][1], a[u][ks][2], a[u][ks][3], ob[ks][0], ob[ks][1]);
            mma_bf16(acc1, a[u][ks + 1][0], a[u][ks + 1][1], a[u][ks + 1][2], a[u][ks + 1][3], ob[ks + 1][0],
                     ob[ks + 1][1]);
          }
          const float v = sel4(acc0, t) + sel4(acc1, t);
          const unsigned long long w = ((unsigned long long)tag << 32) | __float_as_uint(v);
          asm volatile("st.relaxed.gpu.global.b64 [%0], %1;" ::"l"(dst + (size_t)(it * 8 + u) * (kSrcPerBranch * 32)),
                       "l"(w)
                       : "memory");
        }
      }
    }

    if (rank >= kSrcPerBranch - kMTiles) {
      const int mt = rank - (kSrcPerBranch - kMTiles);
      const unsigned long long* srcp = g_part + ((size_t)(br * kMTiles + mt) * kSrcPerBranch + warp * 16) * 32 + lane;
      unsigned long long w[16];
#pragma unroll
      for (int j = 0; j < 16; j++) w[j] = 0;
      uint32_t spins = 0;
      while (true) {
        bool ok = true;
#pragma unroll
        for (int j = 0; j < 16; j++) {
          if ((uint32_t)(w[j] >> 32) != tag)
            asm volatile("ld.relaxed.gpu.global.b64 %0, [%1];" : "=l"(w[j]) : "l"(srcp + j * 32) : "memory");
        }
#pragma unroll
        for (int j = 0; j < 16; j++) ok = ok && ((uint32_t)(w[j] >> 32) == tag);
        if (ok) break;
        if (++spins > kSpinLimit) __trap();
      }
      float v = 0.f;
#pragma unroll
      for (int j = 0; j < 16; j++) v += __uint_as_float((uint32_t)w[j]);
      sts_f32(sbase + kOffFin + (warp * 32 + lane) * 4, v);
      cons_sync();
      if (warp == 0) {
        float r = 0.f;
#pragma unroll
        for (int ww = 0; ww < 4; ww++) r += lds_f32(sbase + kOffFin + (ww * 32 + lane) * 4);
        const int col = mt * 16 + g + 8 * (t >> 1);
        p.out[(t & 1) * (2 * kD) + br * kD + col] = __float2bfloat16_rn(r);
      }
    }
  }
}

typedef CUresult (*EncodeTiledFn)(CUtensorMap*, CUtensorMapDataType, cuuint32_t, void*, const cuuint64_t*,
                                  const cuuint64_t*, const cuuint32_t*, const cuuint32_t*, CUtensorMapInterleave,
                                  CUtensorMapSwizzle, CUtensorMapL2promotion, CUtensorMapFloatOOBfill);

void encode(EncodeTiledFn fn, CUtensorMap* m, const void* base, int rank, const cuuint64_t* dims,
            const cuuint64_t* strides, const cuuint32_t* box) {
  const cuuint32_t es[3] = {1, 1, 1};
  fn(m, CU_TENSOR_MAP_DATA_TYPE_BFLOAT16, rank, const_cast<void*>(base), dims, strides, box, es,
     CU_TENSOR_MAP_INTERLEAVE_NONE, CU_TENSOR_MAP_SWIZZLE_128B, CU_TENSOR_MAP_L2_PROMOTION_NONE,
     CU_TENSOR_MAP_FLOAT_OOB_FILL_NONE);
}

}

extern "C" void kernel_launch(void* const* d_in, const int* in_sizes, int n_in, void* d_out, int out_size) {
  (void)in_sizes;
  (void)n_in;
  (void)out_size;
  static EncodeTiledFn fn = nullptr;
  if (!fn) {
    void* sym = nullptr;
    cudaDriverEntryPointQueryResult qr;
    cudaGetDriverEntryPoint("cuTensorMapEncodeTiled", &sym, cudaEnableDefault, &qr);
    fn = (EncodeTiledFn)sym;
    cudaFuncSetAttribute(fused_decode_kernel, cudaFuncAttributeMaxDynamicSharedMemorySize, kSmemBytes);
  }
  Params p;
  for (int br = 0; br < 2; br++) {
    const void* x = d_in[br * 5 + 0];
    const void* kc = d_in[br * 5 + 1];
    const void* vc = d_in[br * 5 + 2];
    const void* wq = d_in[br * 5 + 3];
    const void* wo = d_in[br * 5 + 4];
    {
      const cuuint64_t dims[2] = {64, (cuuint64_t)2 * kH * kSk * 3};
      const cuuint64_t strides[1] = {128};
      const cuuint32_t box[2] = {64, kTileKeys * 3};
      encode(fn, &p.k[br], kc, 2, dims, strides, box);
      encode(fn, &p.v[br], vc, 2, dims, strides, box);
    }
    {
      const cuuint64_t dims[3] = {64, kHD / 64, kD};
      const cuuint64_t strides[2] = {128, kHD * 2};
      const cuuint32_t box[3] = {64, 3, 64};
      encode(fn, &p.wq[br], wq, 3, dims, strides, box);
    }
    {
      const cuuint64_t dims[2] = {kD, kHD};
      const cuuint64_t strides[1] = {kD * 2};
      const cuuint32_t box[2] = {64, 96};
      encode(fn, &p.wo[br], wo, 2, dims, strides, box);
    }
    p.x[br] = (const __nv_bfloat16*)x;
    p.wq_ptr[br] = (const __nv_bfloat16*)wq;
  }
  p.out = (__nv_bfloat16*)d_out;
  fused_decode_kernel<<<128, kThreads, kSmemBytes>>>(p);
}
```
